```python
import torch

def _softmax(x, axis=-1):
    return torch.softmax(x, dim=axis)

def _gelu(x):
    return torch.nn.functional.gelu(x, approximate='tanh')

def _silu(x):
    return torch.nn.functional.silu(x)

def _sigmoid(x):
    return torch.sigmoid(x)

def _layernorm(x, axis=-1, eps=1e-05):
    m = x.mean(dim=axis, keepdim=True)
    v = x.var(dim=axis, keepdim=True, unbiased=False)
    return (x - m) / torch.sqrt(v + eps)

def _scatter_add(tgt, idx, src, axis=0):
    return tgt.clone().index_add_(axis, idx, src)

def _segment_sum(src, seg, n):
    out = torch.zeros((n,) + src.shape[1:], dtype=src.dtype)
    return out.index_add_(0, seg, src)

def _pad(x, pw):
    flat = tuple((v for pair in reversed(pw) for v in pair))
    return torch.nn.functional.pad(x, flat)
kernel_name = 'recurrent_scan__memory_aug_recurrent_mem_tr__swiglu_ffn__prompt'

def setup_inputs():

    _w = lambda a: (lambda t: t.to(torch.bfloat16) if t.is_floating_point() else t)(torch.as_tensor(a))

    def _A_setup():
        B, S, Dm = (1, 2048, 448)
        H, Dh = (16, 256)
        M, seg = (8, 32)
        seg = min(seg, S)
        S = S // seg * seg
        return {'x': _w((lambda *s: torch.randn(*s, dtype=torch.bfloat16) * 0.05)(B, S, Dm)), 'mem0': _w((lambda *s: torch.randn(*s, dtype=torch.bfloat16) * 0.2)(B, M, Dm)), 'Wq': _w((lambda *s: torch.randn(*s, dtype=torch.bfloat16) * 1.6)(Dm, H, Dh) * Dm ** (-0.5)), 'Wk': _w((lambda *s: torch.randn(*s, dtype=torch.bfloat16) * 1.6)(Dm, H, Dh) * Dm ** (-0.5)), 'Wv': _w((lambda *s: torch.randn(*s, dtype=torch.bfloat16) * 0.2)(Dm, H, Dh) * Dm ** (-0.5)), 'Wo': _w((lambda *s: torch.randn(*s, dtype=torch.bfloat16) * 0.2)(H, Dh, Dm) * (H * Dh) ** (-0.5)), 'seg_len': seg}
    _A_in = _A_setup()

    def _B_setup():
        B, S, D, F = (1, 2048, 448, 1792)
        return {'x': _w((lambda *s: torch.randn(*s, dtype=torch.bfloat16) * 0.05)(B, S, D)), 'w_gate': _w((lambda *s: torch.randn(*s, dtype=torch.bfloat16) * 0.1)(D, F)), 'w_up': _w((lambda *s: torch.randn(*s, dtype=torch.bfloat16) * 0.1)(D, F)), 'w_down': _w((lambda *s: torch.randn(*s, dtype=torch.bfloat16) * 0.1)(F, D))}
    _B_in = _B_setup()
    return {'A_x': _A_in['x'], 'A_mem0': _A_in['mem0'], 'A_Wq': _A_in['Wq'], 'A_Wk': _A_in['Wk'], 'A_Wv': _A_in['Wv'], 'A_Wo': _A_in['Wo'], 'A_seg_len': _A_in['seg_len'], 'B_x': _B_in['x'], 'B_w_gate': _B_in['w_gate'], 'B_w_up': _B_in['w_up'], 'B_w_down': _B_in['w_down']}

def reference(A_x, A_mem0, A_Wq, A_Wk, A_Wv, A_Wo, A_seg_len, B_x, B_w_gate, B_w_up, B_w_down):

    def _A_ref(x, mem0, Wq, Wk, Wv, Wo, seg_len):
        B, S, Dm = x.shape
        H, Dh = (Wq.shape[1], Wq.shape[2])
        M = mem0.shape[1]
        scale = Dh ** (-0.5)
        n_seg = S // seg_len
        L = M + seg_len
        idx = torch.arange(L)
        mask = (idx[:, None] < M) | (idx[:, None] >= idx[None, :])
        mem = mem0
        outs = []
        for s in range(n_seg):
            xs = x[:, s * seg_len:(s + 1) * seg_len, :].clone()
            h = torch.concatenate([mem, xs], axis=1)
            q = torch.einsum('btd,dhe->bhte', h, Wq)
            k = torch.einsum('btd,dhe->bhte', h, Wk)
            v = torch.einsum('btd,dhe->bhte', h, Wv)
            scores = torch.einsum('bhqe,bhke->bhqk', q, k) * scale
            scores = torch.where(mask[None, None], scores, -1000000000.0)
            p = _softmax(scores, axis=-1)
            o = torch.einsum('bhqk,bhke->bhqe', p, v)
            o = torch.einsum('bhte,hed->btd', o, Wo)
            mem = o[:, :M, :].clone()
            outs.append(o[:, M:, :])
        return torch.concatenate(outs, axis=1)

    def _B_ref(x, w_gate, w_up, w_down):
        g = _silu(x @ w_gate)
        u = x @ w_up
        return g * u @ w_down
    x = A_x
    xn = _layernorm(x, axis=-1)
    s = _A_ref(xn, A_mem0, A_Wq, A_Wk, A_Wv, A_Wo, A_seg_len)
    g = _silu(_B_ref(xn, B_w_gate, B_w_up, B_w_down))
    return x + s * g
```

```cpp
#include <cuda_runtime.h>
#include <cuda_bf16.h>
#include <cuda.h>
#include <stdint.h>

#define STREAM_LD 1
#define STREAM_ST 0

namespace {

constexpr int D = 448, NSEG = 64;
constexpr int SLAB = 200704;
constexpr int CHUNK = 7168;
constexpr int QBLK = 8960;
constexpr int VO_OFF = 4 * CHUNK, HBLK = VO_OFF + 4 * QBLK;
constexpr int XTILE = 57344;
constexpr int HTILE = 229376;
constexpr int ACC_STEP = 112 * 32;
constexpr int NWORK = 68, NTAIL = 64, NFFN = 256, NATT = 128;
constexpr float QK_SCALE = 0.0625f * 1.4426950408889634f;

__device__ __align__(1024) uint8_t g_xn[32 * XTILE];
__device__ __align__(1024) uint8_t g_xs[NSEG * 28672];
__device__ __align__(1024) uint8_t g_wall[64 * SLAB];
__device__ __align__(1024) uint8_t g_kv[(NSEG + 1) * 16 * HBLK];
__device__ __align__(1024) unsigned long long g_acc[(NSEG + 2) * ACC_STEP];
__device__ __align__(1024) uint8_t g_h[32 * HTILE];
__device__ __align__(1024) uint8_t g_p[(NSEG + 1) * 32768];
__device__ __align__(1024) uint8_t g_sx[2048 * D * 2];
__device__ __align__(1024) uint8_t g_gx[2048 * D * 2];

struct Ctl {
    unsigned epoch[32];
    unsigned queue[2][2 * 32];
    unsigned cntLN[32];
    unsigned cntA[16 * 32];
    unsigned cntB[16 * 32];
    unsigned prog[128 * 8];
    unsigned cntM[64 * 32];
    unsigned cntH[16 * 32];
    unsigned ticket[256];
    unsigned bmax[64];
};
__device__ __align__(1024) Ctl g_ctl;

#define TR(slot, idx) ((void)0)
#define TT(k) ((void)0)
#define TTARG
#define TTPASS
#define TC(slot, idx) ((void)0)

struct Maps { CUtensorMap q, k, v, o, g, u, d, w; };
enum { T_UP = 0, T_DOWN = 1, T_PV = 3 };

__device__ __forceinline__ uint32_t clk32() { uint32_t c; asm volatile("mov.u32 %0, %%clock;" : "=r"(c)); return c; }
__device__ __forceinline__ uint32_t lds32(uint32_t a) { uint32_t v; asm volatile("ld.shared.b32 %0, [%1];" : "=r"(v) : "r"(a) : "memory"); return v; }
__device__ __forceinline__ uint2 lds64(uint32_t a) { uint2 v; asm volatile("ld.shared.v2.b32 {%0,%1}, [%2];" : "=r"(v.x), "=r"(v.y) : "r"(a) : "memory"); return v; }
__device__ __forceinline__ uint4 lds128(uint32_t a) { uint4 v; asm volatile("ld.shared.v4.b32 {%0,%1,%2,%3}, [%4];" : "=r"(v.x), "=r"(v.y), "=r"(v.z), "=r"(v.w) : "r"(a) : "memory"); return v; }
__device__ __forceinline__ void sts32(uint32_t a, uint32_t v) { asm volatile("st.shared.b32 [%0], %1;" :: "r"(a), "r"(v) : "memory"); }
__device__ __forceinline__ void sts64(uint32_t a, uint32_t x, uint32_t y) { asm volatile("st.shared.v2.b32 [%0], {%1,%2};" :: "r"(a), "r"(x), "r"(y) : "memory"); }
__device__ __forceinline__ void sts128(uint32_t a, uint4 v) { asm volatile("st.shared.v4.b32 [%0], {%1,%2,%3,%4};" :: "r"(a), "r"(v.x), "r"(v.y), "r"(v.z), "r"(v.w) : "memory"); }
__device__ __forceinline__ uint32_t ldcg32(const void* p) { uint32_t v; asm volatile("ld.global.cg.b32 %0, [%1];" : "=r"(v) : "l"(p) : "memory"); return v; }
__device__ __forceinline__ uint4 ldcg128(const void* p) { uint4 v; asm volatile("ld.global.cg.v4.b32 {%0,%1,%2,%3}, [%4];" : "=r"(v.x), "=r"(v.y), "=r"(v.z), "=r"(v.w) : "l"(p) : "memory"); return v; }
__device__ __forceinline__ unsigned ld_acq(const unsigned* p) { unsigned v; asm volatile("ld.acquire.gpu.global.u32 %0, [%1];" : "=r"(v) : "l"(p) : "memory"); return v; }
__device__ __forceinline__ unsigned ld_rlx(const unsigned* p) { unsigned v; asm volatile("ld.relaxed.gpu.global.u32 %0, [%1];" : "=r"(v) : "l"(p) : "memory"); return v; }
__device__ __forceinline__ void red_rel(unsigned* p, unsigned v) { asm volatile("red.release.gpu.global.add.u32 [%0], %1;" :: "l"(p), "r"(v) : "memory"); }
__device__ __forceinline__ void st_rel(unsigned* p, unsigned v) { asm volatile("st.release.gpu.global.u32 [%0], %1;" :: "l"(p), "r"(v) : "memory"); }
__device__ __forceinline__ void fence_async() { asm volatile("fence.proxy.async.global;" ::: "memory"); }
__device__ __forceinline__ void fence_init() { asm volatile("fence.mbarrier_init.release.cluster;\nfence.proxy.async.shared::cta;" ::: "memory"); }
__device__ __forceinline__ int warp_id() { return __shfl_sync(0xffffffffu, (int)(threadIdx.x >> 5), 0); }

__device__ __forceinline__ void bar_sync(int id, int n) { asm volatile("bar.sync %0, %1;" :: "r"(id), "r"(n) : "memory"); }
__device__ __forceinline__ void bar_arrive(int id, int n) { asm volatile("bar.arrive %0, %1;" :: "r"(id), "r"(n) : "memory"); }
__device__ __forceinline__ void cluster_sync() { asm volatile("barrier.cluster.arrive.aligned;\nbarrier.cluster.wait.aligned;" ::: "memory"); }
template <int N> __device__ __forceinline__ void reg_inc() { asm volatile("setmaxnreg.inc.sync.aligned.u32 %0;" :: "n"(N)); }
template <int N> __device__ __forceinline__ void reg_dec() { asm volatile("setmaxnreg.dec.sync.aligned.u32 %0;" :: "n"(N)); }

constexpr uint32_t WAIT_LIMIT = 1u << 27;
__device__ __forceinline__ bool expired(uint32_t t0a) { return clk32() - lds32(t0a) > WAIT_LIMIT; }

__device__ __forceinline__ void mbar_init(uint32_t b, int n) { asm volatile("mbarrier.init.shared::cta.b64 [%0], %1;" :: "r"(b), "r"(n) : "memory"); }
__device__ __forceinline__ void mbar_arrive(uint32_t b) { asm volatile("mbarrier.arrive.shared::cta.b64 _, [%0];" :: "r"(b) : "memory"); }
__device__ __forceinline__ void mbar_expect(uint32_t b, uint32_t tx) { asm volatile("mbarrier.arrive.expect_tx.shared::cta.b64 _, [%0], %1;" :: "r"(b), "r"(tx) : "memory"); }
__device__ __forceinline__ bool mbar_try(uint32_t b, uint32_t par) {
    uint32_t ok;
    asm volatile("{ .reg .pred p; mbarrier.try_wait.parity.shared::cta.b64 p, [%1], %2; selp.u32 %0, 1, 0, p; }" : "=r"(ok) : "r"(b), "r"(par) : "memory");
    return ok;
}
__device__ __forceinline__ void mbar_wait(uint32_t b, uint32_t par, uint32_t t0a) {
    while (!mbar_try(b, par)) { if (expired(t0a)) break; }
}
__device__ __forceinline__ void mbar_wait_warp(uint32_t b, uint32_t par, uint32_t t0a) {
    asm volatile("{ .reg .pred p; .reg .u32 c, t;\n"
                 "W: mbarrier.try_wait.parity.shared::cta.b64 p, [%0], %1;\n"
                 "@p bra.uni E;\n"
                 "mov.u32 c, %%clock; ld.shared.u32 t, [%2]; sub.u32 c, c, t; setp.lt.u32 p, c, %3;\n"
                 "@p bra.uni W;\n"
                 "E: }" :: "r"(b), "r"(par), "r"(t0a), "n"(WAIT_LIMIT) : "memory");
}
__device__ __forceinline__ void flag_wait(const unsigned* p, unsigned target, uint32_t t0a) {
    while ((int)(ld_acq(p) - target) < 0) { if (expired(t0a)) break; }
}
__device__ __forceinline__ void bulk_load(uint32_t dst, const void* src, uint32_t bytes, uint32_t bar) {
    asm volatile("cp.async.bulk.shared::cluster.global.mbarrier::complete_tx::bytes [%0], [%1], %2, [%3];" :: "r"(dst), "l"(src), "r"(bytes), "r"(bar) : "memory");
}
__device__ __forceinline__ uint64_t stream_policy() { uint64_t p; asm("createpolicy.fractional.L2::evict_first.b64 %0, 1.0;" : "=l"(p)); return p; }
__device__ __forceinline__ void bulk_load_stream(uint32_t dst, const void* src, uint32_t bytes, uint32_t bar) {
    asm volatile("cp.async.bulk.shared::cluster.global.mbarrier::complete_tx::bytes.L2::cache_hint [%0], [%1], %2, [%3], %4;"
                 :: "r"(dst), "l"(src), "r"(bytes), "r"(bar), "l"(stream_policy()) : "memory");
}
__device__ __forceinline__ void st_stream(void* p, uint4 v) {
    *(uint4*)p = v;
}
__device__ __forceinline__ void bulk_prefetch(const void* src, uint32_t bytes) {
    asm volatile("cp.async.bulk.prefetch.L2.global [%0], %1;" :: "l"(src), "r"(bytes) : "memory");
}
__device__ __forceinline__ void tma2(uint32_t dst, const CUtensorMap* m, int c0, int c1, uint32_t bar) {
    asm volatile("cp.async.bulk.tensor.2d.shared::cluster.global.tile.mbarrier::complete_tx::bytes [%0], [%1, {%2,%3}], [%4];" :: "r"(dst), "l"(m), "r"(c0), "r"(c1), "r"(bar) : "memory");
}
__device__ __forceinline__ void tma3(uint32_t dst, const CUtensorMap* m, int c0, int c1, int c2, uint32_t bar) {
    asm volatile("cp.async.bulk.tensor.3d.shared::cluster.global.tile.mbarrier::complete_tx::bytes [%0], [%1, {%2,%3,%4}], [%5];" :: "r"(dst), "l"(m), "r"(c0), "r"(c1), "r"(c2), "r"(bar) : "memory");
}
__device__ __forceinline__ void tma2_prefetch(const CUtensorMap* m, int c0, int c1) {
    asm volatile("cp.async.bulk.prefetch.tensor.2d.L2.global.tile [%0, {%1,%2}];" :: "l"(m), "r"(c0), "r"(c1) : "memory");
}
__device__ __forceinline__ void tma3_prefetch(const CUtensorMap* m, int c0, int c1, int c2) {
    asm volatile("cp.async.bulk.prefetch.tensor.3d.L2.global.tile [%0, {%1,%2,%3}];" :: "l"(m), "r"(c0), "r"(c1), "r"(c2) : "memory");
}
__device__ __forceinline__ void st_async64(uint32_t dst, uint32_t x, uint32_t y, uint32_t bar) {
    asm volatile("st.async.weak.shared::cluster.mbarrier::complete_tx::bytes.v2.b32 [%0], {%1,%2}, [%3];" :: "r"(dst), "r"(x), "r"(y), "r"(bar) : "memory");
}

__device__ __forceinline__ uint32_t pack2(float lo, float hi) { uint32_t r; asm("cvt.rn.bf16x2.f32 %0, %1, %2;" : "=r"(r) : "f"(hi), "f"(lo)); return r; }
__device__ __forceinline__ float bflo(uint32_t v) { return __uint_as_float(v << 16); }
__device__ __forceinline__ float bfhi(uint32_t v) { return __uint_as_float(v & 0xffff0000u); }
__device__ __forceinline__ float rbf(float x) { return bflo(pack2(x, 0.f)); }
__device__ __forceinline__ float ex2(float x) { float y; asm("ex2.approx.ftz.f32 %0, %1;" : "=f"(y) : "f"(x)); return y; }
__device__ __forceinline__ float rcp(float x) { float y; asm("rcp.approx.ftz.f32 %0, %1;" : "=f"(y) : "f"(x)); return y; }
#define SILU_TANH 1
__device__ __forceinline__ float silu(float x) {
    const float h = 0.5f * x;
    float t;
    asm("tanh.approx.f32 %0, %1;" : "=f"(t) : "f"(h));
    return fmaf(h, t, h);
}
__device__ __forceinline__ uint32_t movm(uint32_t a) { uint32_t d; asm volatile("movmatrix.sync.aligned.m8n8.trans.b16 %0, %1;" : "=r"(d) : "r"(a)); return d; }
__device__ __forceinline__ void ldsm4(uint32_t (&r)[4], uint32_t a) {
    asm volatile("ldmatrix.sync.aligned.m8n8.x4.shared.b16 {%0,%1,%2,%3}, [%4];" : "=r"(r[0]), "=r"(r[1]), "=r"(r[2]), "=r"(r[3]) : "r"(a) : "memory");
}
__device__ __forceinline__ void ldsm4t(uint32_t& r0, uint32_t& r1, uint32_t& r2, uint32_t& r3, uint32_t a) {
    asm volatile("ldmatrix.sync.aligned.m8n8.x4.trans.shared.b16 {%0,%1,%2,%3}, [%4];" : "=r"(r0), "=r"(r1), "=r"(r2), "=r"(r3) : "r"(a) : "memory");
}
__device__ __forceinline__ void ldsm2t(uint32_t& r0, uint32_t& r1, uint32_t a) {
    asm volatile("ldmatrix.sync.aligned.m8n8.x2.trans.shared.b16 {%0,%1}, [%2];" : "=r"(r0), "=r"(r1) : "r"(a) : "memory");
}
__device__ __forceinline__ void mma16(float (&c)[4], uint32_t a0, uint32_t a1, uint32_t a2, uint32_t a3, uint32_t b0, uint32_t b1) {
    asm("mma.sync.aligned.m16n8k16.row.col.f32.bf16.bf16.f32 {%0,%1,%2,%3}, {%4,%5,%6,%7}, {%8,%9}, {%0,%1,%2,%3};"
        : "+f"(c[0]), "+f"(c[1]), "+f"(c[2]), "+f"(c[3]) : "r"(a0), "r"(a1), "r"(a2), "r"(a3), "r"(b0), "r"(b1));
}
__device__ __forceinline__ void mma8(float (&c)[4], uint32_t a0, uint32_t a1, uint32_t b0) {
    asm("mma.sync.aligned.m16n8k8.row.col.f32.bf16.bf16.f32 {%0,%1,%2,%3}, {%4,%5}, {%6}, {%0,%1,%2,%3};"
        : "+f"(c[0]), "+f"(c[1]), "+f"(c[2]), "+f"(c[3]) : "r"(a0), "r"(a1), "r"(b0));
}

__device__ __forceinline__ void mma16v(float (&c)[4], uint32_t a0, uint32_t a1, uint32_t a2, uint32_t a3, uint32_t b0, uint32_t b1) {
    asm volatile("mma.sync.aligned.m16n8k16.row.col.f32.bf16.bf16.f32 {%0,%1,%2,%3}, {%4,%5,%6,%7}, {%8,%9}, {%0,%1,%2,%3};"
        : "+f"(c[0]), "+f"(c[1]), "+f"(c[2]), "+f"(c[3]) : "r"(a0), "r"(a1), "r"(a2), "r"(a3), "r"(b0), "r"(b1));
}

__device__ __forceinline__ uint64_t mdesc(uint32_t addr, uint32_t lbo, uint32_t sbo, uint32_t swz) {
    return (uint64_t)((addr & 0x3FFFF) >> 4) | ((uint64_t)(lbo >> 4) << 16) | ((uint64_t)(sbo >> 4) << 32) | ((uint64_t)swz << 62);
}
__device__ __forceinline__ void wg_fence() { asm volatile("wgmma.fence.sync.aligned;" ::: "memory"); }
__device__ __forceinline__ void wg_commit() { asm volatile("wgmma.commit_group.sync.aligned;" ::: "memory"); }
template <int N> __device__ __forceinline__ void wg_wait() { asm volatile("wgmma.wait_group.sync.aligned %0;" :: "n"(N) : "memory"); }
template <int N> __device__ __forceinline__ void acc_zero(float (&d)[N]) {
#pragma unroll
    for (int i = 0; i < N; i++) d[i] = 0.f;
}
template <int N> __device__ __forceinline__ void acc_fence(float (&d)[N]) {
#pragma unroll
    for (int i = 0; i < N; i++) asm volatile("" : "+f"(d[i]) :: "memory");
}

template <int TA, int TB>
__device__ __forceinline__ void wgmma_n112(float (&d)[56], uint64_t da, uint64_t db, int acc) {
    asm volatile("{ .reg .pred p; setp.ne.b32 p, %58, 0;\n"
        "wgmma.mma_async.sync.aligned.m64n112k16.f32.bf16.bf16 "
        "{%0,%1,%2,%3,%4,%5,%6,%7,%8,%9,%10,%11,%12,%13,%14,%15,"
        "%16,%17,%18,%19,%20,%21,%22,%23,%24,%25,%26,%27,%28,%29,%30,%31,"
        "%32,%33,%34,%35,%36,%37,%38,%39,%40,%41,%42,%43,%44,%45,%46,%47,"
        "%48,%49,%50,%51,%52,%53,%54,%55}, "
        "%56, %57, p, 1, 1, %59, %60; }"
        : "+f"(d[0]), "+f"(d[1]), "+f"(d[2]), "+f"(d[3]), "+f"(d[4]), "+f"(d[5]), "+f"(d[6]), "+f"(d[7]),
          "+f"(d[8]), "+f"(d[9]), "+f"(d[10]), "+f"(d[11]), "+f"(d[12]), "+f"(d[13]), "+f"(d[14]), "+f"(d[15]),
          "+f"(d[16]), "+f"(d[17]), "+f"(d[18]), "+f"(d[19]), "+f"(d[20]), "+f"(d[21]), "+f"(d[22]), "+f"(d[23]),
          "+f"(d[24]), "+f"(d[25]), "+f"(d[26]), "+f"(d[27]), "+f"(d[28]), "+f"(d[29]), "+f"(d[30]), "+f"(d[31]),
          "+f"(d[32]), "+f"(d[33]), "+f"(d[34]), "+f"(d[35]), "+f"(d[36]), "+f"(d[37]), "+f"(d[38]), "+f"(d[39]),
          "+f"(d[40]), "+f"(d[41]), "+f"(d[42]), "+f"(d[43]), "+f"(d[44]), "+f"(d[45]), "+f"(d[46]), "+f"(d[47]),
          "+f"(d[48]), "+f"(d[49]), "+f"(d[50]), "+f"(d[51]), "+f"(d[52]), "+f"(d[53]), "+f"(d[54]), "+f"(d[55])
        : "l"(da), "l"(db), "r"(acc), "n"(TA), "n"(TB));
}
template <int TA, int TB>
__device__ __forceinline__ void wgmma_n224(float (&d)[112], uint64_t da, uint64_t db, int acc) {
    asm volatile("{ .reg .pred p; setp.ne.b32 p, %114, 0;\n"
        "wgmma.mma_async.sync.aligned.m64n224k16.f32.bf16.bf16 "
        "{%0,%1,%2,%3,%4,%5,%6,%7,%8,%9,%10,%11,%12,%13,%14,%15,"
        "%16,%17,%18,%19,%20,%21,%22,%23,%24,%25,%26,%27,%28,%29,%30,%31,"
        "%32,%33,%34,%35,%36,%37,%38,%39,%40,%41,%42,%43,%44,%45,%46,%47,"
        "%48,%49,%50,%51,%52,%53,%54,%55,%56,%57,%58,%59,%60,%61,%62,%63,"
        "%64,%65,%66,%67,%68,%69,%70,%71,%72,%73,%74,%75,%76,%77,%78,%79,"
        "%80,%81,%82,%83,%84,%85,%86,%87,%88,%89,%90,%91,%92,%93,%94,%95,"
        "%96,%97,%98,%99,%100,%101,%102,%103,%104,%105,%106,%107,%108,%109,%110,%111}, "
        "%112, %113, p, 1, 1, %115, %116; }"
        : "+f"(d[0]), "+f"(d[1]), "+f"(d[2]), "+f"(d[3]), "+f"(d[4]), "+f"(d[5]), "+f"(d[6]), "+f"(d[7]),
          "+f"(d[8]), "+f"(d[9]), "+f"(d[10]), "+f"(d[11]), "+f"(d[12]), "+f"(d[13]), "+f"(d[14]), "+f"(d[15]),
          "+f"(d[16]), "+f"(d[17]), "+f"(d[18]), "+f"(d[19]), "+f"(d[20]), "+f"(d[21]), "+f"(d[22]), "+f"(d[23]),
          "+f"(d[24]), "+f"(d[25]), "+f"(d[26]), "+f"(d[27]), "+f"(d[28]), "+f"(d[29]), "+f"(d[30]), "+f"(d[31]),
          "+f"(d[32]), "+f"(d[33]), "+f"(d[34]), "+f"(d[35]), "+f"(d[36]), "+f"(d[37]), "+f"(d[38]), "+f"(d[39]),
          "+f"(d[40]), "+f"(d[41]), "+f"(d[42]), "+f"(d[43]), "+f"(d[44]), "+f"(d[45]), "+f"(d[46]), "+f"(d[47]),
          "+f"(d[48]), "+f"(d[49]), "+f"(d[50]), "+f"(d[51]), "+f"(d[52]), "+f"(d[53]), "+f"(d[54]), "+f"(d[55]),
          "+f"(d[56]), "+f"(d[57]), "+f"(d[58]), "+f"(d[59]), "+f"(d[60]), "+f"(d[61]), "+f"(d[62]), "+f"(d[63]),
          "+f"(d[64]), "+f"(d[65]), "+f"(d[66]), "+f"(d[67]), "+f"(d[68]), "+f"(d[69]), "+f"(d[70]), "+f"(d[71]),
          "+f"(d[72]), "+f"(d[73]), "+f"(d[74]), "+f"(d[75]), "+f"(d[76]), "+f"(d[77]), "+f"(d[78]), "+f"(d[79]),
          "+f"(d[80]), "+f"(d[81]), "+f"(d[82]), "+f"(d[83]), "+f"(d[84]), "+f"(d[85]), "+f"(d[86]), "+f"(d[87]),
          "+f"(d[88]), "+f"(d[89]), "+f"(d[90]), "+f"(d[91]), "+f"(d[92]), "+f"(d[93]), "+f"(d[94]), "+f"(d[95]),
          "+f"(d[96]), "+f"(d[97]), "+f"(d[98]), "+f"(d[99]), "+f"(d[100]), "+f"(d[101]), "+f"(d[102]), "+f"(d[103]),
          "+f"(d[104]), "+f"(d[105]), "+f"(d[106]), "+f"(d[107]), "+f"(d[108]), "+f"(d[109]), "+f"(d[110]), "+f"(d[111])
        : "l"(da), "l"(db), "r"(acc), "n"(TA), "n"(TB));
}
template <int TA, int TB>
__device__ __forceinline__ void wgmma_n256(float (&d)[128], uint64_t da, uint64_t db, int acc) {
    asm volatile("{ .reg .pred p; setp.ne.b32 p, %130, 0;\n"
        "wgmma.mma_async.sync.aligned.m64n256k16.f32.bf16.bf16 "
        "{%0,%1,%2,%3,%4,%5,%6,%7,%8,%9,%10,%11,%12,%13,%14,%15,"
        "%16,%17,%18,%19,%20,%21,%22,%23,%24,%25,%26,%27,%28,%29,%30,%31,"
        "%32,%33,%34,%35,%36,%37,%38,%39,%40,%41,%42,%43,%44,%45,%46,%47,"
        "%48,%49,%50,%51,%52,%53,%54,%55,%56,%57,%58,%59,%60,%61,%62,%63,"
        "%64,%65,%66,%67,%68,%69,%70,%71,%72,%73,%74,%75,%76,%77,%78,%79,"
        "%80,%81,%82,%83,%84,%85,%86,%87,%88,%89,%90,%91,%92,%93,%94,%95,"
        "%96,%97,%98,%99,%100,%101,%102,%103,%104,%105,%106,%107,%108,%109,%110,%111,"
        "%112,%113,%114,%115,%116,%117,%118,%119,%120,%121,%122,%123,%124,%125,%126,%127}, "
        "%128, %129, p, 1, 1, %131, %132; }"
        : "+f"(d[0]), "+f"(d[1]), "+f"(d[2]), "+f"(d[3]), "+f"(d[4]), "+f"(d[5]), "+f"(d[6]), "+f"(d[7]),
          "+f"(d[8]), "+f"(d[9]), "+f"(d[10]), "+f"(d[11]), "+f"(d[12]), "+f"(d[13]), "+f"(d[14]), "+f"(d[15]),
          "+f"(d[16]), "+f"(d[17]), "+f"(d[18]), "+f"(d[19]), "+f"(d[20]), "+f"(d[21]), "+f"(d[22]), "+f"(d[23]),
          "+f"(d[24]), "+f"(d[25]), "+f"(d[26]), "+f"(d[27]), "+f"(d[28]), "+f"(d[29]), "+f"(d[30]), "+f"(d[31]),
          "+f"(d[32]), "+f"(d[33]), "+f"(d[34]), "+f"(d[35]), "+f"(d[36]), "+f"(d[37]), "+f"(d[38]), "+f"(d[39]),
          "+f"(d[40]), "+f"(d[41]), "+f"(d[42]), "+f"(d[43]), "+f"(d[44]), "+f"(d[45]), "+f"(d[46]), "+f"(d[47]),
          "+f"(d[48]), "+f"(d[49]), "+f"(d[50]), "+f"(d[51]), "+f"(d[52]), "+f"(d[53]), "+f"(d[54]), "+f"(d[55]),
          "+f"(d[56]), "+f"(d[57]), "+f"(d[58]), "+f"(d[59]), "+f"(d[60]), "+f"(d[61]), "+f"(d[62]), "+f"(d[63]),
          "+f"(d[64]), "+f"(d[65]), "+f"(d[66]), "+f"(d[67]), "+f"(d[68]), "+f"(d[69]), "+f"(d[70]), "+f"(d[71]),
          "+f"(d[72]), "+f"(d[73]), "+f"(d[74]), "+f"(d[75]), "+f"(d[76]), "+f"(d[77]), "+f"(d[78]), "+f"(d[79]),
          "+f"(d[80]), "+f"(d[81]), "+f"(d[82]), "+f"(d[83]), "+f"(d[84]), "+f"(d[85]), "+f"(d[86]), "+f"(d[87]),
          "+f"(d[88]), "+f"(d[89]), "+f"(d[90]), "+f"(d[91]), "+f"(d[92]), "+f"(d[93]), "+f"(d[94]), "+f"(d[95]),
          "+f"(d[96]), "+f"(d[97]), "+f"(d[98]), "+f"(d[99]), "+f"(d[100]), "+f"(d[101]), "+f"(d[102]), "+f"(d[103]),
          "+f"(d[104]), "+f"(d[105]), "+f"(d[106]), "+f"(d[107]), "+f"(d[108]), "+f"(d[109]), "+f"(d[110]), "+f"(d[111]),
          "+f"(d[112]), "+f"(d[113]), "+f"(d[114]), "+f"(d[115]), "+f"(d[116]), "+f"(d[117]), "+f"(d[118]), "+f"(d[119]),
          "+f"(d[120]), "+f"(d[121]), "+f"(d[122]), "+f"(d[123]), "+f"(d[124]), "+f"(d[125]), "+f"(d[126]), "+f"(d[127])
        : "l"(da), "l"(db), "r"(acc), "n"(TA), "n"(TB));
}

constexpr uint32_t AB_A = 57344;

template <int TYPE>
__device__ __forceinline__ void ab_load_tile(const Maps* maps, int h, int tile, uint32_t dst, uint32_t bar) {
    if (TYPE == 0) tma3(dst, &maps->q, 0, 64 * tile, 4 * h, bar);
    else tma2(dst, &maps->o, 64 * tile, 256 * h, bar);
}
template <int TYPE>
__device__ __forceinline__ void ab_issue(const Maps* maps, int h, int q, uint32_t sb, uint32_t bars) {
#pragma unroll
    for (int i = 0; i < 7; i++) mbar_init(bars + 8 * i, 1);
    fence_init();
    mbar_expect(bars, 57344 + 32768);
    tma3(sb, TYPE == 0 ? &maps->k : &maps->v, 0, 112 * q, 4 * h, bars);
#pragma unroll 1
    for (int t = 0; t < 7; t++) {
        if (t > 0) mbar_expect(bars + 8 * t, 32768);
        if (t < 5) ab_load_tile<TYPE>(maps, h, t, sb + AB_A + t * 32768, bars + 8 * t);
        else if ((q & 1) == t - 5) { if (TYPE == 0) tma3_prefetch(&maps->q, 0, 64 * t, 4 * h); else tma2_prefetch(&maps->o, 64 * t, 256 * h); }
    }
}
template <int TYPE, int NWG>
__device__ __forceinline__ float ab_compute(const Maps* maps, int h, int q, uint32_t sb, uint32_t bars, int wg, int barid, uint32_t t0a) {
    const int lane = threadIdx.x & 31, warp = (threadIdx.x >> 5) & 3;
    float mx = 0.f;
#pragma unroll 1
    for (int t = wg; t < 7; t += NWG) {
        const uint32_t sa = sb + AB_A + (t < 5 ? t : t - 5) * 32768;
        float acc[56];
        acc_zero(acc);
        if (t == wg) mbar_wait_warp(bars, 0, t0a);
        mbar_wait_warp(bars + 8 * t, 0, t0a);
        if (threadIdx.x == 0 && t == 0) TR(196, (TYPE * 64 + 4 * h + q) * 4);
        wg_fence();
#pragma unroll
        for (int kk = 0; kk < 16; kk++)
            wgmma_n112<TYPE, 0>(acc, mdesc(sa + (TYPE ? kk * 2048 : (kk >> 2) * 8192 + (kk & 3) * 32), 16, 1024, 1),
                                mdesc(sb + (kk >> 2) * 14336 + (kk & 3) * 32, 16, 1024, 1), 1);
        wg_commit();
        wg_wait<0>();
        acc_fence(acc);
        if (threadIdx.x == 0 && t == 0) TR(196, (TYPE * 64 + 4 * h + q) * 4 + 1);
        if (threadIdx.x == 0 && t >= 4) TR(196, (TYPE * 64 + 4 * h + q) * 4 + 3);
        if (t < 2) {
            bar_sync(barid, 128);
            if ((threadIdx.x & 127) == 0) ab_load_tile<TYPE>(maps, h, t + 5, sa, bars + 8 * (t + 5));
        }
#pragma unroll
        for (int hi = 0; hi < 2; hi++) {
            const int ng = 8 * t + 2 * warp + hi, half = ng >= 28;
            uint32_t* dst = (uint32_t*)(g_wall + (size_t)(4 * h + 2 * TYPE + half) * SLAB + (14 * q * 28 + ng - 28 * half) * 128) + lane;
#pragma unroll
            for (int u = 0; u < 14; u++) {
                float a = acc[4 * u + 2 * hi], b = acc[4 * u + 2 * hi + 1];
                if (TYPE == 0) { a *= QK_SCALE; b *= QK_SCALE; }
                else mx = fmaxf(mx, fmaxf(fabsf(a), fabsf(b)));
                dst[u * 28 * 32] = pack2(a, b);
            }
        }
        if (threadIdx.x == 0 && t == 0) TR(196, (TYPE * 64 + 4 * h + q) * 4 + 2);
    }
    return mx;
}

constexpr int NST = 4, RSTG = 4 * CHUNK;
#define NSX 0
#define NSY 4
#define NSZ 12
#define RX 160
#define RY 112
#define RZ_ 208
#define RH 32
#define USE_GO 0
#define WGX 2
#define WGY 0
#define WGZ 1
#define SPLITY 0
#define XLAG 1
#define NCZ 3
#define TAILX 8
#define TAILY 6
#define NRED 1
constexpr uint32_t SB = 1024;
constexpr uint32_t C_MEMT = SB, C_SPART = SB + 7168, C_SMM = SB + 9216, C_SMT = SB + 10240, C_SMTL = SB + 11264, C_PT = SB + 12288,
                   C_SMAX = SB + 13056, C_SINV = SB + 13072, C_KQM = SB + 13312, C_VOM = SB + 20480, C_TSB = SB + 27648, C_KQS = SB + 37888, C_WB = SB + 39680,
                   C_RING = C_WB + 4 * (NSX + NSY + NSZ) * 512, C_STAGE = SB + 27648,
                   C_BAR = C_STAGE + SLAB, C_T0 = C_BAR + 256, C_SMEM = C_BAR - SB + 512;
static_assert(C_RING + NST * RSTG <= C_BAR && C_RING % 128 == 0, "chain shared memory");
constexpr uint32_t CB_SMT = C_BAR + 64, CB_SMM = C_BAR + 72, CB_EXP = C_BAR + 80, CB_TS = C_BAR + 88, CB_KV = C_BAR + 104,
                   CB_W = C_BAR + 136;
enum { B_RED = 1, B_MQ = 2, B_ALLX = 6, B_ALLY = 7, B_GO = 8, B_SPART = 9, B_KQ = 10, B_Z = 11, B_PT = 12, B_SMTL = 13, B_PUSHED = 14, B_AB = 12 };
#define PX 2
#define PY 2
#define PZ 3
#define DELAY_A 8
#define DELAY_L 1
#define DELAY_B 6

#define TS(i) ((void)0)
template <class T> __device__ __forceinline__ T pin(T v) { asm volatile("" : "+r"(v)); return v; }
template <class T> __device__ __forceinline__ T* pin(T* v) { asm volatile("" : "+l"(v)); return v; }
__device__ __forceinline__ uint32_t remote(uint32_t local, uint32_t rank) { return __byte_perm(local, rank, 0x4210); }
template <int N, class T> __device__ __forceinline__ T* delayed(T* p, uint32_t dep) {
    uint32_t lo = (uint32_t)(uintptr_t)p ^ dep;
#pragma unroll
    for (int i = 0; i < 2 * N; i++) asm volatile("shfl.sync.bfly.b32 %0, %0, 1, 31, 0xffffffff;" : "+r"(lo) :: "memory");
    return (T*)(((uintptr_t)p & ~(uintptr_t)0xFFFFFFFFu) | (pin(lo) ^ dep));
}
__device__ __forceinline__ void ld_words(uint4& v, const void* p) {
    asm volatile("{ .reg .b64 a, b; ld.relaxed.gpu.global.v2.u64 {a, b}, [%4]; mov.b64 {%0,%1}, a; mov.b64 {%2,%3}, b; }"
                 : "=r"(v.x), "=r"(v.y), "=r"(v.z), "=r"(v.w) : "l"(p) : "memory");
}
constexpr float MAGIC = 12582912.f;
__device__ __forceinline__ uint2 encode_pair(float a, float b) { return make_uint2(__float_as_uint(b) * 32u + 1u, __float_as_uint(a)); }
__device__ __forceinline__ uint32_t decode_word(uint32_t lo, uint32_t hi, float inv) {
    return pack2((float)(int)(hi - 0xB4000006u) * inv, (float)((int)(lo >> 5) - (1 << 26)) * inv);
}
template <int N, class F>
__device__ __forceinline__ void poll_rows(uint2 (&d)[N], const uint8_t* p, float inv, uint32_t t0a, F overlap) {
    uint4 v[N];
#pragma unroll
    for (int i = 0; i < N; i++) ld_words(v[i], p + i * 1024);
    overlap();
    while (true) {
        uint32_t m = v[0].x, ok;
#pragma unroll
        for (int i = 1; i < N; i++) m &= v[i].x & v[i].z;
        asm volatile("{ .reg .pred p; .reg .b32 c; and.b32 c, %1, %2; and.b32 c, c, 16; setp.ne.u32 p, c, 0;\n"
                     "vote.sync.all.pred p, p, 0xffffffff; selp.u32 %0, 1, 0, p; }" : "=r"(ok) : "r"(m), "r"(v[0].z));
#pragma unroll
        for (int i = 0; i < N; i++) d[i] = make_uint2(pin(decode_word(v[i].x, v[i].y, inv)), pin(decode_word(v[i].z, v[i].w, inv)));
        if (ok) break;
#pragma unroll
        for (int i = 0; i < N; i++) ld_words(v[i], p + i * 1024);
        if (__any_sync(0xffffffffu, expired(t0a))) break;
    }
}
__device__ __forceinline__ int seg_slot(int s) { return s < 0 ? NSEG : s; }
__device__ __forceinline__ int acc_off(int c) { return (c >> 2) * 32 + (c & 3) * 4; }

__device__ __forceinline__ int perm_row(int lane) { return (lane & 7) | ((lane & 8) << 1) | ((lane & 16) >> 1); }

__device__ __forceinline__ void load_quarter(uint32_t (&b)[7][2], uint32_t perm, uint32_t nat) {
    ldsm4t(b[0][0], b[0][1], b[1][0], b[1][1], perm + C_MEMT);
    ldsm4t(b[2][0], b[2][1], b[3][0], b[3][1], perm + C_MEMT + 512);
    ldsm4t(b[4][0], b[4][1], b[5][0], b[5][1], perm + C_MEMT + 1024);
    ldsm2t(b[6][0], b[6][1], nat + C_MEMT + 1536);
}
__device__ __forceinline__ float xor_max3(float v, float extra) {
    return fmaxf(fmaxf(fmaxf(v, extra), __shfl_xor_sync(0xffffffffu, v, 1)), fmaxf(__shfl_xor_sync(0xffffffffu, v, 2), __shfl_xor_sync(0xffffffffu, v, 3)));
}
__device__ __forceinline__ float xor_sum3(float v, float first) {
    return (first + __shfl_xor_sync(0xffffffffu, v, 1)) + (__shfl_xor_sync(0xffffffffu, v, 2) + __shfl_xor_sync(0xffffffffu, v, 3));
}
template <int NT, int NC, int NS, int TAIL, bool SPLIT = false>
struct Weights {
    static constexpr int NF = 7 * NT, NR = NF - NS, NP = NT / NC, LAST = NT - NC * (NP - 1);
    uint32_t w[NR][4];
    uint4 tw[2];
    static __device__ constexpr int pass(int f) { return f / (7 * NC) < NP ? f / (7 * NC) : NP - 1; }
    static __device__ constexpr int width(int p) { return p < NP - 1 ? NC : LAST; }
    static __device__ constexpr int slot(int f) { return (f - pass(f) * 7 * NC) % width(pass(f)); }
    static __device__ constexpr int kstep(int f) { return (f - pass(f) * 7 * NC) / width(pass(f)); }
    static __device__ constexpr int before(int f) { return f < NF - TAIL ? (f * NS) / (NF - TAIL) : NS; }
    static __device__ constexpr bool shared(int f) { return before(f + 1) != before(f); }
    __device__ __forceinline__ void load(uint32_t src, uint32_t wsm) {
        const int lane = threadIdx.x & 31;
        const uint32_t row = src + (lane & 15) * 16, far = (lane >> 4) * 1792;
        uint32_t t[NS > 0 ? NS : 1][4];
#pragma unroll
        for (int f = 0; f < NF; f++) {
            const int k = kstep(f), first = k < 6 ? 2 * (k & ~1) + (k & 1) : 12;
            const uint32_t a = row + (k < 6 ? 2 * far : far) + first * 1792 + (pass(f) * NC + slot(f)) * 256;
            if (shared(f)) ldsm4(t[before(f) % (NS > 0 ? NS : 1)], a);
            else ldsm4(w[(f - before(f)) % NR], a);
        }
        bar_sync(B_RED, 384);
        asm volatile("barrier.cluster.arrive.relaxed.aligned;\nbarrier.cluster.wait.aligned;" ::: "memory");
#pragma unroll
        for (int i = 0; i < NS; i++) sts128(wsm + i * 512, make_uint4(t[i][0], t[i][1], t[i][2], t[i][3]));
    }
    __device__ __forceinline__ void prefetch(uint32_t wsm) {
        if (NS > 0) tw[0] = lds128(wsm);
        if (NS > 1) tw[1] = lds128(wsm + 512);
    }
    template <class H, class F>
    __device__ __forceinline__ void gemm(const uint32_t (&b)[7][2], uint32_t wsm, float zero, H hook, F done) {
#pragma unroll
        for (int p = 0; p < NP; p++) {
            float acc[SPLIT ? 2 * LAST : LAST][4];
#pragma unroll
            for (int t = 0; t < (SPLIT ? 2 * LAST : LAST); t++) acc[t][0] = acc[t][1] = acc[t][2] = acc[t][3] = zero;
#pragma unroll
            for (int f = p * 7 * NC; f < p * 7 * NC + 7 * width(p); f++) {
                const int ns = before(f), r = (f - ns) % NR, k = kstep(f), c = slot(f) + (SPLIT && (k & 1) ? LAST : 0);
                if (f == NF - TAIL) hook();
                if (shared(f)) {
                    mma16v(acc[c], tw[ns & 1].x, tw[ns & 1].y, tw[ns & 1].z, tw[ns & 1].w, b[k][0], b[k][1]);
                    if (ns + 2 < NS) tw[ns & 1] = lds128(wsm + (ns + 2) * 512);
                } else {
                    mma16v(acc[c], w[r][0], w[r][1], w[r][2], w[r][3], b[k][0], b[k][1]);
                }
            }
#pragma unroll
            for (int t = 0; t < width(p); t++) {
                if (SPLIT) {
#pragma unroll
                    for (int i = 0; i < 4; i++) acc[t][i] += acc[(LAST + t) % (SPLIT ? 2 * LAST : LAST)][i];
                }
                done(p * NC + t, pack2(acc[t][0], acc[t][1]), pack2(acc[t][2], acc[t][3]));
            }
            if (p + 1 < NP) zero = __uint_as_float(__float_as_uint(acc[0][0]) & pin(0u));
        }
    }
};
__device__ __forceinline__ uint2 add4_bf16(const uint2 (&u)[4]) {
    return make_uint2(pack2((bflo(u[0].x) + bflo(u[1].x)) + (bflo(u[2].x) + bflo(u[3].x)), (bfhi(u[0].x) + bfhi(u[1].x)) + (bfhi(u[2].x) + bfhi(u[3].x))),
                      pack2((bflo(u[0].y) + bflo(u[1].y)) + (bflo(u[2].y) + bflo(u[3].y)), (bfhi(u[0].y) + bfhi(u[1].y)) + (bfhi(u[2].y) + bfhi(u[3].y))));
}
__device__ __forceinline__ uint2 sum4_bf16(uint32_t a) {
    const uint2 u[4] = {lds64(a), lds64(a + 1792), lds64(a + 3584), lds64(a + 5376)};
    return add4_bf16(u);
}
__device__ __forceinline__ float2 sum4_f32(uint32_t a) {
    const uint2 u0 = lds64(a), u1 = lds64(a + 256), u2 = lds64(a + 512), u3 = lds64(a + 768);
    return make_float2((__uint_as_float(u0.x) + __uint_as_float(u1.x)) + (__uint_as_float(u2.x) + __uint_as_float(u3.x)),
                       (__uint_as_float(u0.y) + __uint_as_float(u1.y)) + (__uint_as_float(u2.y) + __uint_as_float(u3.y)));
}

template <bool MEM>
__device__ __forceinline__ void token_tile_pair(uint32_t own, uint32_t l8, int q, int j, int s) {
    const uint32_t ring = C_RING + (s & (NST - 1)) * RSTG, lane8 = l8 - own;
    const int rt = !MEM && j > 0;
    const uint32_t xa = own + ring + 3 * CHUNK + rt * 256 + (lane8 & 128) * 4 + (lane8 & 127) * 2;
    const uint32_t kb = l8 + (MEM ? C_KQS : ring + 2 * CHUNK + (j & 2) * 1792);
    float c0[4] = {0.f, 0.f, 0.f, 0.f}, c1[4] = {0.f, 0.f, 0.f, 0.f};
#pragma unroll
    for (int k = 0; k < 7; k += 2) {
        uint32_t a[4], b[4];
        if (MEM) {
#pragma unroll
            for (int kk = k; kk < min(k + 2, 7); kk++) {
                const uint2 v = lds64(kb + kk * 256);
                ldsm4(a, xa + kk * 1024);
                ldsm4(b, xa + kk * 1024 + 256);
                mma16v(c0, a[0], a[1], a[2], a[3], v.x, v.y);
                mma16v(c1, b[0], b[1], b[2], b[3], v.x, v.y);
            }
        } else if (k < 6) {
            ldsm4(a, xa + k * 1024);
            const uint4 u = lds128(kb + lane8 + k * 256), v = lds128(kb + lane8 + 1792 + k * 256);
            ldsm4(b, xa + k * 1024 + 1024);
            mma16v(c0, a[0], a[1], a[2], a[3], u.x, u.y);
            mma16v(c1, a[0], a[1], a[2], a[3], v.x, v.y);
            mma16v(c0, b[0], b[1], b[2], b[3], u.z, u.w);
            mma16v(c1, b[0], b[1], b[2], b[3], v.z, v.w);
        } else {
            ldsm4(a, xa + k * 1024);
            const uint2 u = lds64(kb + 1536), v = lds64(kb + 1792 + 1536);
            mma16v(c0, a[0], a[1], a[2], a[3], u.x, u.y);
            mma16v(c1, a[0], a[1], a[2], a[3], v.x, v.y);
        }
    }
    const uint32_t dst = lane8 + C_TSB + (s & 1) * 5120 + (q * 5 + (MEM ? 0 : 1 + (j & 2))) * 256, bar = CB_TS + 8 * (s & 1);
    const uint32_t r0 = rt << 25, r1 = MEM ? 2 << 24 : r0, d1 = dst + (MEM ? 0 : 256);
    st_async64(r0 + dst, __float_as_uint(c0[0]), __float_as_uint(c0[1]), r0 + bar);
    st_async64(r0 + (1 << 24) + dst, __float_as_uint(c0[2]), __float_as_uint(c0[3]), r0 + (1 << 24) + bar);
    if (MEM || j == 1) st_async64(r1 + d1, __float_as_uint(c1[0]), __float_as_uint(c1[1]), r1 + bar);
    st_async64(r1 + (1 << 24) + d1, __float_as_uint(c1[2]), __float_as_uint(c1[3]), r1 + (1 << 24) + bar);
    __syncwarp();
    if (lane8 == 0) mbar_arrive(own + CB_EXP);
}

__device__ __forceinline__ void token_scores(uint32_t own, uint32_t l8, int q, int j, int s) {
    if (j == 3) token_tile_pair<true>(own, l8, q, j, s);
    else token_tile_pair<false>(own, l8, q, j, s);
}

template <bool Y>
__device__ __forceinline__ void chain_key_warp(int q, int j) {
    constexpr int NT = Y ? 3 : 4, T0 = Y ? 4 : 0;
    const int lane = threadIdx.x & 31;
    const uint32_t own = q << 24, t0a = own + C_T0;
    const uint32_t nj = pin(own + lane * 16 + j * 1792);
    const uint32_t wsm = nj - j * 1792 + C_WB + (Y ? 4 * NSX + j * NSY : j * NSX) * 512;
    Weights<NT, NT, Y ? NSY : NSX, Y ? TAILY : TAILX, Y && SPLITY> W;
    mbar_wait_warp(own + CB_W + 8 * j, 0, t0a);
    W.load(own + C_STAGE + j * 25088 + T0 * 256, wsm);
    const uint32_t rj = pin(own + lane * 8 + j * 1792), l8 = rj - j * 1792;
    const uint32_t pj = pin(own + perm_row(lane) * 16 + j * 1792);
    const uint32_t pT = pin(own + perm_row(lane) * 16 + q * 1792 + T0 * 256);
    const uint32_t nT = Y ? pin(own + lane * 16 + q * 1792 + T0 * 256) : 0;
    const uint32_t sp = pin(own + lane * 8 + (T0 + j) * 256 + C_SPART);
    const uint32_t sdst = lane * 8 + q * 256 + C_SMM;
    const uint8_t* pp = pin((const uint8_t*)(g_acc + acc_off(112 * j + (Y ? 16 * PX : 0) + (lane >> 1)) + (lane & 1) * 2));
#pragma unroll 1
    for (int s = -1; s < NSEG; s++) {
        if (s >= 0) {
            bar_sync(B_RED, 384);
            TS(8);
            if (!Y) token_scores(own, l8, q, j, s - 1);
        }
        const uint32_t invb = lds32(own + C_SINV + (s > 0 ? 0 : 8));
        const float inv = __uint_as_float(invb);
        pp = delayed<Y ? DELAY_A : DELAY_L>(pp, invb);
        uint2 v[Y ? PY : PX];
        TS(0);
        poll_rows(v, pp, inv, t0a, [&] { W.prefetch(wsm); });
        TS(1);
#pragma unroll
        for (int i = 0; i < (Y ? PY : PX); i++) sts64(rj + C_MEMT + (Y ? PX * 256 : 0) + i * 256, v[i].x, v[i].y);
        pp += s >= 0 ? ACC_STEP * 8 : 0;
        bar_arrive(Y ? B_ALLX : B_ALLY, 384);
        bar_sync(B_MQ + j, 96);
        TS(2);
        uint32_t b[7][2];
        uint32_t pb = pj;
        if (!Y) {
#pragma unroll
            for (int i = 0; i < 2 * XLAG; i++) asm volatile("shfl.sync.bfly.b32 %0, %0, 1, 31, 0xffffffff;" : "+r"(pb) :: "memory");
        }
        load_quarter(b, pb, nj);
        uint32_t m0[NT], m1[NT], a0, a1, a2, a3, a4, a5, a6, a7;
        W.gemm(b, wsm, 0.f, [&] {
            bar_sync(Y ? B_ALLY : B_ALLX, 384);
            ldsm4t(a0, a1, a2, a3, pT + C_MEMT);
            if (!Y) ldsm4t(a4, a5, a6, a7, pT + C_MEMT + 512);
            else ldsm2t(a4, a5, nT + C_MEMT + 512);
        }, [&](int t, uint32_t lo, uint32_t hi) { m0[t] = movm(lo); m1[t] = movm(hi); });
        TS(3);
        if (USE_GO == 1) bar_arrive(B_GO, 384);
        float c0[4] = {0.f, 0.f, 0.f, 0.f}, c1[4] = {0.f, 0.f, 0.f, 0.f};
        mma16(c0, a0, a1, a2, a3, m0[0], m1[0]);
        mma16(c1, a0, a1, a2, a3, m0[1], m1[1]);
        if (!Y) {
            mma16(c0, a4, a5, a6, a7, m0[2], m1[2]);
            mma16(c1, a4, a5, a6, a7, m0[NT - 1], m1[NT - 1]);
        } else {
            mma8(c0, a4, a5, m0[2]);
            mma8(c1, a4, a5, m1[2]);
        }
        sts64(sp, __float_as_uint(c0[0] + c1[2]), __float_as_uint(c0[1] + c1[3]));
        TS(5);
        if (Y && j < NRED) {
            bar_sync(B_SPART, 256);
            TS(6);
            if (USE_GO == 2) bar_arrive(B_GO, 128 + 32 * NRED);
            const float2 u = sum4_f32(l8 + C_SPART), v = sum4_f32(l8 + C_SPART + 1024);
#pragma unroll
            for (int i = 0; i < 4 / NRED; i++) {
                const uint32_t r = (q + 1 + j * (4 / NRED) + i) & 3;
                st_async64(remote(sdst, r), __float_as_uint(u.x + v.x), __float_as_uint(u.y + v.y), (r << 24) + CB_SMM);
            }
            TS(7);
            bar_arrive(B_PUSHED, 256);
        } else {
            bar_arrive(B_SPART, 256);
            bar_sync(B_PUSHED, 256);
        }
#pragma unroll
        for (int t = 0; t < NT; t++) sts64(rj + C_KQM + (T0 + t) * 256, m0[t], m1[t]);
        if (Y) {
            bar_sync(B_KQ, 256);
            const uint2 u = sum4_bf16(l8 + C_KQM + j * 256), v = sum4_bf16(l8 + C_KQM + min(4 + j, 6) * 256);
            sts64(l8 + C_KQS + j * 256, u.x, u.y);
            sts64(l8 + C_KQS + min(4 + j, 6) * 256, v.x, v.y);
        } else {
            bar_arrive(B_KQ, 256);
        }
    }
    bar_sync(B_RED, 384);
    if (!Y) token_scores(own, l8, q, j, NSEG - 1);
}

__device__ __forceinline__ void chain_value_warp(int h, int q, int j) {
    const int lane = threadIdx.x & 31;
    const uint32_t own = q << 24, t0a = own + C_T0;
    const uint32_t l8 = pin(own + lane * 8), l16 = pin(own + lane * 16);
    const uint32_t wsm = l16 + C_WB + (4 * (NSX + NSY) + j * NSZ) * 512;
    Weights<7, NCZ, NSZ, 4> W;
    mbar_wait_warp(own + CB_W + 32 + 8 * j, 0, t0a);
    W.load(own + C_STAGE + (4 + j) * 25088, wsm);
    const uint32_t rj = pin(own + lane * 8 + j * 1792);
    const uint32_t pj = pin(own + perm_row(lane) * 16 + j * 1792);
    const bool second = rj - l8 < 3 * 1792;
    const uint32_t nothing = pin(0u);
    uint8_t* pp = pin((uint8_t*)(g_acc + acc_off(112 * j + 16 * (7 - PZ) + (lane >> 1)) + (lane & 1) * 2));
    const int rdelta = pin(8 * (acc_off(112 * q + 32 * j + (lane >> 2)) + (lane & 3) - acc_off(112 * j + 16 * (7 - PZ) + (lane >> 1)) - (lane & 1) * 2));
    const int t1 = min(2 * j + 1, 6);
    uint2 m0[4], m1[4];
    auto export_values = [&](int s) {
        uint8_t* ep = g_kv + ((seg_slot(s) * 16 + h) * HBLK + VO_OFF + q * QBLK + CHUNK) + (l8 & 255);
        *(uint2*)(ep + j * 512) = add4_bf16(m0);
        *(uint2*)(ep + t1 * 256) = add4_bf16(m1);
        __syncwarp();
        if (l8 == own) mbar_arrive(own + CB_EXP);
    };
#pragma unroll 1
    for (int s = -1; s < NSEG; s++) {
        const uint32_t ring = C_RING + (s & (NST - 1)) * RSTG;
        uint4 k0, k1, k2;
        uint2 k3;
        auto load_keys = [&] {
            if (s >= 0) mbar_wait_warp(own + CB_KV + 8 * (s & (NST - 1)), (s / NST) & 1, t0a);
            k0 = lds128(l16 + ring + j * 1792); k1 = lds128(l16 + ring + j * 1792 + 512); k2 = lds128(l16 + ring + j * 1792 + 1024);
            k3 = lds64(rj + ring + 1536);
        };
        const uint32_t invb = lds32(own + C_SINV + (s > 0 ? 0 : 8));
        const float inv = __uint_as_float(invb);
        pp = delayed<DELAY_B>(pp, invb);
        uint2 v[PZ];
        TS(0);
        poll_rows(v, pp, inv, t0a, [&] {
            if (s >= 0) export_values(s - 1);
            load_keys();
        });
        TS(1);
#pragma unroll
        for (int i = 0; i < PZ; i++) sts64(rj + C_MEMT + (7 - PZ + i) * 256, v[i].x, v[i].y);
        pp += s >= 0 ? ACC_STEP * 8 : 0;
        bar_arrive(B_ALLX, 384);
        bar_arrive(B_ALLY, 384);
        bar_sync(B_MQ + j, 96);
        TS(2);
        uint32_t b[7][2];
        load_quarter(b, pj, l16 + j * 1792);
        {
            float c[8][4];
#pragma unroll
            for (int i = 0; i < 8; i++) c[i][0] = c[i][1] = c[i][2] = c[i][3] = 0.f;
            mma16v(c[0], b[0][0], b[0][1], b[1][0], b[1][1], k0.x, k0.y);
            mma16v(c[1], b[0][0], b[0][1], b[1][0], b[1][1], k0.z, k0.w);
            mma16v(c[2], b[2][0], b[2][1], b[3][0], b[3][1], k1.x, k1.y);
            mma16v(c[3], b[2][0], b[2][1], b[3][0], b[3][1], k1.z, k1.w);
            mma16v(c[4], b[4][0], b[4][1], b[5][0], b[5][1], k2.x, k2.y);
            mma16v(c[5], b[4][0], b[4][1], b[5][0], b[5][1], k2.z, k2.w);
            mma8(c[6], b[6][0], b[6][1], k3.x);
            mma8(c[7], b[6][0], b[6][1], k3.y);
            uint32_t m = b[0][0], n = b[0][1];
#pragma unroll
            for (int i = 1; i < 7; i++) {
                asm("max.xorsign.abs.bf16x2 %0, %0, %1;" : "+r"(m) : "r"(b[i][0]));
                asm("max.xorsign.abs.bf16x2 %0, %0, %1;" : "+r"(n) : "r"(b[i][1]));
            }
            asm("max.xorsign.abs.bf16x2 %0, %0, %1;" : "+r"(m) : "r"(n));
            sts32(own + C_SMAX + 4 * j, __reduce_max_sync(0xffffffffu, max(m & 0x7FFF0000u, (m << 16) & 0x7FFF0000u)));
            sts64(l8 + C_SMTL + j * 256, __float_as_uint(((c[0][0] + c[1][2]) + (c[2][0] + c[3][2])) + ((c[4][0] + c[5][2]) + (c[6][0] + c[7][2]))),
                  __float_as_uint(((c[0][1] + c[1][3]) + (c[2][1] + c[3][3])) + ((c[4][1] + c[5][3]) + (c[6][1] + c[7][3]))));
            TS(3);
            bar_arrive(B_SMTL, 160);
        }
        W.prefetch(wsm);
        float zero = 0.f;
        if (USE_GO) {
            bar_sync(B_GO, USE_GO == 1 ? 384 : 128 + 32 * NRED);
            asm volatile("shfl.sync.bfly.b32 %0, %0, 1, 31, 0xffffffff;" : "+f"(zero) :: "memory");
        }
        W.gemm(b, wsm, zero, [] {}, [&](int t, uint32_t lo, uint32_t hi) { sts64(rj + C_VOM + t * 256, lo, hi); });
        TS(4);
        bar_sync(B_Z, 128);
        TS(5);
#pragma unroll
        for (int i = 0; i < 4; i++) { m0[i] = lds64(l8 + C_VOM + j * 512 + i * 1792); m1[i] = lds64(l8 + C_VOM + t1 * 256 + i * 1792); }
        const uint32_t vo = l16 + ring + CHUNK;
        const uint4 va = lds128(vo + j * 1024), vb = lds128(vo + 3584 + j * 1024), vc = lds128(vo + t1 * 512), vd = lds128(vo + 3584 + t1 * 512);
        uint8_t* rp = pin(pp + (s < 0 ? rdelta + (NSEG + 1) * ACC_STEP * 8 : rdelta));
        TS(6);
        mbar_wait_warp(own + CB_SMM, ~s & 1, t0a);
        const float2 sm = sum4_f32(l8 + C_SMM);
        bar_sync(B_PT, 160);
        TS(8);
        const uint2 ml = lds64(l8 + C_PT + 512);
        const uint4 p = lds128(l16 + C_PT);
        const float scale = __uint_as_float(lds32(own + C_SINV + 4));
        TS(7);
        const float mt = __uint_as_float(ml.x), lt = __uint_as_float(ml.y);
        const float m = xor_max3(fmaxf(sm.x, sm.y), mt);
        const float p0 = ex2(sm.x - m), p1 = ex2(sm.y - m), al = ex2(mt - m);
        float o0[4] = {0.f, 0.f, 0.f, 0.f}, o1[4] = {0.f, 0.f, 0.f, 0.f};
        mma16v(o0, va.x, va.y, va.z, va.w, p.x, p.y);
        mma16v(o1, vc.x, vc.y, vc.z, vc.w, p.x, p.y);
        mma16v(o0, vb.x, vb.y, vb.z, vb.w, p.z, p.w);
        mma16v(o1, vd.x, vd.y, vd.z, vd.w, p.z, p.w);
        const float ps = p0 + p1;
        const float il = rcp(xor_sum3(ps, fmaf(al, lt, ps)));
        const float f = (al * scale) * il;
        const float f0 = __shfl_sync(0xffffffffu, f, l8 & 24), f1 = __shfl_sync(0xffffffffu, f, (l8 & 24) + 4);
        const uint32_t pm = pack2((p0 * scale) * il, (p1 * scale) * il);
        float n0[4] = {0.f, 0.f, 0.f, 0.f}, n1[4] = {0.f, 0.f, 0.f, 0.f}, n2[4] = {0.f, 0.f, 0.f, 0.f}, n3[4] = {0.f, 0.f, 0.f, 0.f};
        mma16v(n0, m0[0].x, m0[0].y, m0[1].x, m0[1].y, pm, pm);
        mma16v(n1, m1[0].x, m1[0].y, m1[1].x, m1[1].y, pm, pm);
        mma16v(n2, m0[2].x, m0[2].y, m0[3].x, m0[3].y, pm, pm);
        mma16v(n3, m1[2].x, m1[2].y, m1[3].x, m1[3].y, pm, pm);
        uint2 r[4];
        r[0] = encode_pair(fmaf(o0[0], f0, MAGIC) + (n0[0] + n2[0]), fmaf(o0[1], f1, MAGIC) + (n0[1] + n2[1]));
        r[1] = encode_pair(fmaf(o0[2], f0, MAGIC) + (n0[2] + n2[2]), fmaf(o0[3], f1, MAGIC) + (n0[3] + n2[3]));
        r[2] = encode_pair(fmaf(o1[0], f0, MAGIC) + (n1[0] + n3[0]), fmaf(o1[1], f1, MAGIC) + (n1[1] + n3[1]));
        r[3] = encode_pair(fmaf(o1[2], f0, MAGIC) + (n1[2] + n3[2]), fmaf(o1[3], f1, MAGIC) + (n1[3] + n3[3]));
        r[0].x |= r[2].x & nothing;
        r[1].x |= r[3].x & nothing;
        asm volatile("{ .reg .pred p; .reg .b64 a, b, c, d; setp.ne.u32 p, %9, 0;\n"
                     "mov.b64 a, {%1, %2}; mov.b64 b, {%3, %4}; mov.b64 c, {%5, %6}; mov.b64 d, {%7, %8};\n"
                     "red.relaxed.gpu.global.add.u64 [%0], a; red.relaxed.gpu.global.add.u64 [%0 + 512], b;\n"
                     "@p red.relaxed.gpu.global.add.u64 [%0 + 1024], c; @p red.relaxed.gpu.global.add.u64 [%0 + 1536], d; }"
                     :: "l"(rp), "r"(r[0].x), "r"(r[0].y), "r"(r[1].x), "r"(r[1].y), "r"(r[2].x), "r"(r[2].y), "r"(r[3].x), "r"(r[3].y),
                        "r"((uint32_t)second) : "memory");
        TS(9);
        bar_arrive(B_RED, 384);
    }
    export_values(NSEG - 1);
}

__device__ __forceinline__ bool kv_ready(int h, int q, int seg, unsigned e) {
    const int tile = seg >> 1;
    const unsigned target = e * 64 + (tile >> 1) + 1;
    const unsigned* p = &g_ctl.prog[(8 * h + (tile & 1)) * 8];
    const unsigned a = ld_rlx(p), b = ld_rlx(p + 16), c = ld_rlx(p + (2 + (q >> 1)) * 16);
    return (int)(a - target) >= 0 && (int)(b - target) >= 0 && (int)(c - target) >= 0;
}
__device__ __forceinline__ void kv_fill(int h, int q, unsigned e, int& issued, int must, int lim) {
    const uint32_t own = q << 24;
    while (issued <= lim) {
        if ((issued & 1) == 0) {
            bool ok = kv_ready(h, q, issued, e);
            while (!ok && issued <= must && !expired(own + C_T0)) ok = kv_ready(h, q, issued, e);
            if (!ok && issued > must) break;
            fence_async();
        }
        const uint32_t bar = own + CB_KV + 8 * (issued % NST), dst = own + C_RING + (issued % NST) * RSTG;
        const uint8_t* src = g_kv + (size_t)(issued * 16 + h) * HBLK;
        mbar_expect(bar, RSTG);
#pragma unroll 1
        for (int i = 0; i < 4; i++) bulk_load(dst + i * 1792, src + i * CHUNK + q * 1792, 1792, bar);
        bulk_load(dst + CHUNK, src + VO_OFF + q * QBLK, CHUNK, bar);
        bulk_load_stream(dst + 2 * CHUNK, src + q * CHUNK, CHUNK, bar);
        bulk_load(dst + 3 * CHUNK, g_xs + issued * 28672 + q * CHUNK, CHUNK, bar);
        issued++;
    }
}
__device__ __forceinline__ void chain_token_warp(int q, int ebase) {
    const int lane = threadIdx.x & 31;
    const uint32_t own = q << 24, l8 = own + lane * 8;
#pragma unroll 1
    for (int s = -1; s < NSEG; s++) {
        bar_sync(B_SMTL, 160);
        TS(0);
        const float2 u = sum4_f32(l8 + C_SMTL);
#pragma unroll
        for (int i = 1; i <= 4; i++) {
            const uint32_t r = (q + i) & 3;
            st_async64(remote(l8, r) + C_SMT + q * 256, __float_as_uint(u.x), __float_as_uint(u.y), (r << 24) + CB_SMT);
        }
        TS(1);
        const uint4 mq = lds128(own + C_SMAX);
        const int ex = min(max(ebase + (int)(max(max(max(mq.x, mq.y), max(mq.z, mq.w)), 0x3f7fffffu) >> 23) - 126, -90), 100);
        sts64(own + C_SINV, (uint32_t)(105 + ex) << 23, (uint32_t)(149 - ex) << 23);
        mbar_wait_warp(own + CB_SMT, ~s & 1, own + C_T0);
        TS(2);
        float x[8];
#pragma unroll
        for (int i = 0; i < 4; i++) {
            const uint2 v = lds64(l8 + C_SMT + i * 256);
            x[2 * i] = __uint_as_float(v.x); x[2 * i + 1] = __uint_as_float(v.y);
        }
        const float ma = fmaxf(fmaxf(fmaxf(x[0], x[1]), fmaxf(x[2], x[3])), fmaxf(fmaxf(x[4], x[5]), fmaxf(x[6], x[7])));
        const float m = xor_max3(ma, ma);
#pragma unroll
        for (int i = 0; i < 8; i++) x[i] = ex2(x[i] - m);
        const float la = ((x[0] + x[1]) + (x[2] + x[3])) + ((x[4] + x[5]) + (x[6] + x[7]));
        const float l = xor_sum3(la, la);
        sts128(own + lane * 16 + C_PT, make_uint4(pack2(x[0], x[1]), pack2(x[2], x[3]), pack2(x[4], x[5]), pack2(x[6], x[7])));
        sts64(l8 + C_PT + 512, __float_as_uint(m), __float_as_uint(l));
        TS(3);
        bar_arrive(B_PT, 160);
    }
}

__device__ __forceinline__ void chain_row_warp(int h, int q) {
    const int lane = threadIdx.x & 31, g = lane >> 2, r = lane & 3;
    const uint32_t own = q << 24, l8 = own + lane * 8;
#pragma unroll 1
    for (int s = -1; s < NSEG; s++) {
        uint32_t* dst = (uint32_t*)(g_p + seg_slot(s) * 32768 + h * 2048 + lane * 16);
        mbar_wait_warp(own + CB_TS + 8 * (s & 1), ((s + 1) >> 1) & 1, own + C_T0);
        float x[10], m = -INFINITY;
#pragma unroll
        for (int i = 0; i < 5; i++) {
            const uint32_t a = l8 + C_TSB + (s & 1) * 5120 + min(i, q + 1) * 256;
            const uint2 u0 = lds64(a), u1 = lds64(a + 1280), u2 = lds64(a + 2560), u3 = lds64(a + 3840);
            x[2 * i] = (__uint_as_float(u0.x) + __uint_as_float(u1.x)) + (__uint_as_float(u2.x) + __uint_as_float(u3.x));
            x[2 * i + 1] = (__uint_as_float(u0.y) + __uint_as_float(u1.y)) + (__uint_as_float(u2.y) + __uint_as_float(u3.y));
            if (8 * (i - 1) + 2 * r > 8 * q + g) x[2 * i] = -INFINITY;
            if (8 * (i - 1) + 2 * r + 1 > 8 * q + g) x[2 * i + 1] = -INFINITY;
            m = fmaxf(m, fmaxf(x[2 * i], x[2 * i + 1]));
        }
        m = xor_max3(m, m);
        float l = 0.f;
#pragma unroll
        for (int i = 0; i < 10; i++) { x[i] = ex2(x[i] - m); l += x[i]; }
        const float il = rcp(xor_sum3(l, l));
        dst[384 + q] = pack2(x[0] * il, x[1] * il);
        dst[(q >> 1) * 128 + (q & 1)] = pack2(x[2] * il, x[3] * il);
        dst[(q >> 1) * 128 + 2 + (q & 1)] = pack2(x[4] * il, x[5] * il);
        if (q >= 2) {
            dst[256 + (q & 1)] = pack2(x[6] * il, x[7] * il);
            dst[258 + (q & 1)] = pack2(x[8] * il, x[9] * il);
        }
        __syncwarp();
        if (lane == 0) mbar_arrive(own + CB_EXP);
    }
}

__device__ __forceinline__ void chain_helper(int h, int q, unsigned e) {
    const uint32_t own = q << 24, t0a = own + C_T0;
    int issued = 0;
#pragma unroll 1
    for (int s = -1; s <= NSEG; s++) {
        if (s >= 0) mbar_wait(own + CB_EXP, s & 1, t0a);
        if (s < NSEG) {
            mbar_expect(own + CB_SMT, 1024);
            mbar_expect(own + CB_SMM, 1024);
            mbar_expect(own + CB_TS + 8 * (s & 1), (q + 2) * 1024);
            const unsigned long long* a = g_acc + min(s + 2, NSEG) * ACC_STEP + blockIdx.x * 32;
            asm volatile("prefetch.global.L2 [%0];" :: "l"(a));
            if (blockIdx.x < 48) asm volatile("prefetch.global.L2 [%0];" :: "l"(a + 64 * 32));
            kv_fill(h, q, e, issued, s < 0 ? -1 : min(s + 1, NSEG - 1), min(s + NST - 1, NSEG - 1));
        }
        if (s > 0) {
            red_rel(&g_ctl.cntM[(s - 1) * 32], 1);
            TR(64 + blockIdx.x, s - 1);
        }
        if (s == 8 && blockIdx.x == 0) {
            flag_wait(g_ctl.cntLN, NWORK * e, t0a);
            g_ctl.epoch[0] = e;
            g_ctl.queue[(e + 1) & 1][0] = g_ctl.queue[(e + 1) & 1][32] = 0;
        }
    }
}

__global__ void __cluster_dims__(4, 1, 1) __launch_bounds__(512, 1)
chain_kernel(const __grid_constant__ Maps maps, const __nv_bfloat16* x, const __nv_bfloat16* __restrict__ mem0, int mode) {
    extern __shared__ __align__(1024) uint8_t smem[];
    const uint32_t sb = (uint32_t)__cvta_generic_to_shared(smem);
    const uint32_t t0a = sb - SB + C_T0, bars = sb - SB + C_BAR;
    const int tid = threadIdx.x, lane = tid & 31, warp = warp_id(), wg = warp >> 2;
    const int h = blockIdx.x >> 2, q = blockIdx.x & 3;
    const uint32_t own = q << 24;
    if (sb != own + SB) __trap();
    asm volatile("griddepcontrol.launch_dependents;");
    if (tid == 480) {
        if (mode & 1) ab_issue<0>(&maps, h, q, sb, bars);
    } else if (tid == 0) {
        sts32(t0a, clk32());
    } else if (tid == 32) {
        TR(128, blockIdx.x);
        mbar_init(own + CB_SMT, 1);
        mbar_init(own + CB_SMM, 1);
        mbar_init(own + CB_EXP, 9);
        mbar_init(own + CB_TS, 1);
        mbar_init(own + CB_TS + 8, 1);
        for (int i = 0; i < NST; i++) mbar_init(own + CB_KV + 8 * i, 1);
        for (int i = 0; i < 8; i++) mbar_init(own + CB_W + 8 * i, 1);
        fence_init();
    } else if (tid == 64 && (mode & 1)) {
        bulk_prefetch(x + (size_t)blockIdx.x * 32 * D, 32 * D * 2);
    }
    float m0[8];
    if (tid < D) {
        uint32_t mx = 0;
#pragma unroll
        for (int i = 0; i < 8; i++) {
            m0[i] = __bfloat162float(mem0[i * D + tid]);
            mx = max(mx, __float_as_uint(fabsf(m0[i])));
        }
        mx = __reduce_max_sync(0xffffffffu, mx);
        if (lane == 0) sts32(t0a + 64 + 4 * warp, mx);
    }
    const unsigned e = ld_rlx(g_ctl.epoch) + 1;
    __syncthreads();
    const int ex0 = min(max((int)(__reduce_max_sync(0xffffffffu, lds32(t0a + 64 + 4 * min(lane, 13))) >> 23), 40), 240);
    if (mode & 1) {
        if (blockIdx.x == 0 && tid < D) {
            const float sc = __uint_as_float((uint32_t)(279 - ex0) << 23);
#pragma unroll
            for (int i = 0; i < 4; i++)
                g_acc[acc_off(tid) + i] = ((unsigned long long)(__float2int_rn(m0[2 * i] * sc) + 0xB4000006u) << 32) |
                                          ((uint32_t)(__float2int_rn(m0[2 * i + 1] * sc) + (1 << 26)) * 32u + 16u);
        }
        uint4* z = (uint4*)(g_acc + (blockIdx.x + 1) * ACC_STEP);
        for (int i = tid; i < 896; i += 512) z[(i >> 3) * 16 + (i & 7)] = make_uint4(0, 0, 0, 0);
        ab_compute<0, 4>(&maps, h, q, sb, bars, wg, B_AB + wg, t0a);
        __syncthreads();
        if (tid == 480) { red_rel(&g_ctl.cntA[h * 32], 1); TR(129, blockIdx.x); }
    }
    if (!(mode & 2)) return;
    if (tid == 0) sts32(own + C_SINV + 8, (uint32_t)(ex0 - 25) << 23);
    if (lane == 0 && warp < 2) {
        flag_wait(warp ? &g_ctl.cntB[h * 32] : &g_ctl.cntA[h * 32], 4 * e, t0a);
        fence_async();
#pragma unroll 1
        for (int j = 0; j < 4; j++) {
            const uint32_t bar = own + CB_W + 8 * (4 * warp + j);
            mbar_expect(bar, 25088);
            tma3(own + C_STAGE + (4 * warp + j) * 25088, &maps.w, 0, 14 * (q & 1), (4 * h + 2 * warp + (q >> 1)) * 56 + 14 * j, bar);
        }
    }
    if (warp == 13) flag_wait(lane < 16 ? &g_ctl.cntA[lane * 32] : &g_ctl.cntB[(lane - 16) * 32], 4 * e, t0a);
    __syncthreads();
    if (tid == 0) TR(130, blockIdx.x);
    if (wg == WGX) {
        reg_inc<RX>();
        chain_key_warp<false>(q, warp & 3);
        cluster_sync();
    } else if (wg == WGY) {
        reg_dec<RY>();
        chain_key_warp<true>(q, warp & 3);
        cluster_sync();
    } else if (wg == WGZ) {
        reg_inc<RZ_>();
        chain_value_warp(h, q, warp & 3);
        cluster_sync();
    } else {
        reg_dec<RH>();
        asm volatile("barrier.cluster.arrive.relaxed.aligned;\nbarrier.cluster.wait.aligned;" ::: "memory");
        if (warp == 13) {
            const uint32_t bm = __reduce_max_sync(0xffffffffu, max(ldcg32(&g_ctl.bmax[lane]), ldcg32(&g_ctl.bmax[32 + lane])));
            chain_token_warp(q, (int)(bm >> 23) - 126 + 9);
        }
        if (warp == 14) chain_row_warp(h, q);
        if (tid == 384) chain_helper(h, q, e);
        __syncwarp();
        cluster_sync();
    }
}

constexpr uint32_t W_RING = SLAB, W_STAGE = 49152, W_DBUF = 4 * W_STAGE, W_BAR = 229376, W_MISC = W_BAR + 512, W_SMEM = W_MISC + 512;
constexpr uint32_t WB_SLAB = 64, WB_FULL = 120, WB_EMPTY = 176, WB_GFULL = 232, WB_GEMPTY = 264, WB_TFULL = 296, WB_TEMPTY = 312,
                   WB_DFULL = 328, WB_DEMPTY = 336, WB_WDONE = 352, WB_PFULL = 360, WB_PEMPTY = 376, WB_NEXT = 392;
constexpr uint32_t WM_T0 = 0, WM_TASK = 8, WM_TICK = 16, WM_MAX = 32, WM_POST = 96;
#define P_AHEAD 1
#define RANK0 4
#define FFN_SPARES 0
#define SPARE_FFN 1
constexpr uint32_t GATE_READY = 0x10000, GATE_NEAR = 0x20000;
enum { N_TURN = 1, N_WG = 3, N_CONS = 7, N_LN = 8 };

__device__ __forceinline__ uint32_t mul2(uint32_t a, uint32_t b) { uint32_t r; asm("mul.rn.bf16x2 %0, %1, %2;" : "=r"(r) : "r"(a), "r"(b)); return r; }
__device__ __forceinline__ float quad_sum(float v) { v += __shfl_xor_sync(0xffffffffu, v, 1); return v + __shfl_xor_sync(0xffffffffu, v, 2); }

__device__ __forceinline__ uint32_t combine(uint32_t xv, uint32_t s, uint32_t g) {
    uint32_t r;
    asm("add.rn.bf16x2 %0, %1, %2;" : "=r"(r) : "r"(xv), "r"(mul2(s, g)));
    return r;
}
__device__ __forceinline__ uint4 combine4(uint4 x, uint4 s, uint4 g) {
    return make_uint4(combine(x.x, s.x, g.x), combine(x.y, s.y, g.y), combine(x.z, s.z, g.z), combine(x.w, s.w, g.w));
}

__device__ __forceinline__ void post(uint32_t sb, int& pn, uint32_t code) {
    const uint32_t bars = sb + W_BAR, misc = sb + W_MISC;
    if (threadIdx.x == 0) {
        mbar_wait(bars + WB_PEMPTY + 8 * (pn & 1), ((pn >> 1) & 1) ^ 1, misc + WM_T0);
        sts32(misc + WM_POST + 4 * (pn & 1), code);
    }
    __syncwarp();
    if ((threadIdx.x & 31) == 0) mbar_arrive(bars + WB_PFULL + 8 * (pn & 1));
    pn++;
}
__device__ __forceinline__ void publisher(uint32_t sb, const __nv_bfloat16* x, __nv_bfloat16* out) {
    const uint32_t bars = sb + W_BAR, misc = sb + W_MISC;
    const int lane = threadIdx.x & 31;
#pragma unroll 1
    for (int n = 0;; n++) {
        mbar_wait_warp(bars + WB_PFULL + 8 * (n & 1), (n >> 1) & 1, misc + WM_T0);
        const uint32_t code = lds32(misc + WM_POST + 4 * (n & 1));
        __syncwarp();
        if (lane == 0) mbar_arrive(bars + WB_PEMPTY + 8 * (n & 1));
        if (code == 0xFFFFu || expired(misc + WM_T0)) break;
        const int a = (code >> 4) & 1023, b = code & 15;
        if (((code >> 14) & 3) == T_UP) {
            if (lane == 0) red_rel(&g_ctl.cntH[a * 32], 1);
        } else {
            unsigned old = 0;
            if (lane < 2) asm volatile("atom.acq_rel.gpu.global.add.u32 %0, [%1], 1;" : "=r"(old) : "l"(&g_ctl.ticket[2 * (2 * a + lane) + b]) : "memory");
            const unsigned todo = code & GATE_READY ? 0u : __ballot_sync(0xffffffffu, old & 1);
#pragma unroll 1
            for (int i = lane; i < 896; i += 32) {
                const int row = i / 28, off = ((32 * a + row) * D + 224 * b + 8 * (i - 28 * row)) * 2;
                if ((todo >> (row >> 4)) & 1)
                    *(uint4*)((uint8_t*)out + off) = combine4(ldcg128((const uint8_t*)x + off), ldcg128(g_sx + off), ldcg128(g_gx + off));
                if (!todo) break;
            }
        }
        __syncwarp();
    }
}

__device__ __forceinline__ void ln_load(uint4 (&v)[14], const __nv_bfloat16* __restrict__ x, int seg, int warp, int lane) {
    const uint4* xr = (const uint4*)(x + (size_t)(32 * seg + 8 * warp + (lane >> 2)) * D) + (lane & 3);
#pragma unroll
    for (int j = 0; j < 14; j++) v[j] = ldcg128(xr + 4 * j);
}
__device__ __forceinline__ uint32_t ln_pair(uint32_t v, uint32_t mb2, float rden) {
    uint32_t d;
    asm("sub.rn.bf16x2 %0, %1, %2;" : "=r"(d) : "r"(v), "r"(mb2));
    return pack2(bflo(d) * rden, bfhi(d) * rden);
}
__device__ __forceinline__ void ln_finish(const uint4 (&v)[14], int seg, int warp, int lane) {
    float s0 = 0.f, s1 = 0.f;
#pragma unroll
    for (int j = 0; j < 14; j++) {
        s0 += (bflo(v[j].x) + bflo(v[j].y)) + (bflo(v[j].z) + bflo(v[j].w));
        s1 += (bfhi(v[j].x) + bfhi(v[j].y)) + (bfhi(v[j].z) + bfhi(v[j].w));
    }
    const float mean = quad_sum(s0 + s1) * (1.f / D);
    s0 = s1 = 0.f;
#pragma unroll
    for (int j = 0; j < 14; j++) {
        const uint32_t u[4] = {v[j].x, v[j].y, v[j].z, v[j].w};
#pragma unroll
        for (int i = 0; i < 4; i++) {
            const float a = bflo(u[i]) - mean, b = bfhi(u[i]) - mean;
            s0 = fmaf(a, a, s0);
            s1 = fmaf(b, b, s1);
        }
    }
    const float rden = 1.f / rbf(sqrtf(rbf(rbf(quad_sum(s0 + s1) * (1.f / D)) + 1e-5f)));
    const uint32_t mb2 = pack2(mean, mean);
    uint8_t* d0 = g_xn + (size_t)(seg >> 1) * XTILE + ((seg & 1) * 4 + warp) * 128 + (lane >> 2) * 16 + (lane & 3) * 1024;
    uint8_t* d1 = g_xs + (size_t)seg * 28672 + warp * 128 + (lane >> 2) * 16 + (lane & 3) * 512;
#pragma unroll
    for (int j = 0; j < 14; j++) {
        const uint4 t = make_uint4(ln_pair(v[j].x, mb2, rden), ln_pair(v[j].y, mb2, rden), ln_pair(v[j].z, mb2, rden), ln_pair(v[j].w, mb2, rden));
        *(uint4*)(d0 + j * 4096) = t;
        *(uint4*)(d1 + j * 2048) = t;
    }
}

__device__ __forceinline__ void kv_consumer(uint32_t sb, int w, unsigned e) {
    const int lane = threadIdx.x & 31, warp = (threadIdx.x >> 5) & 3, wg = threadIdx.x >> 7;
    const uint32_t bars = sb + W_BAR, t0a = sb + W_MISC + WM_T0;
    const int h = w >> 2, half = w & 1;
    const bool TYPE = w & 2;
#pragma unroll 1
    for (int t = wg; t < 32; t += 2) {
        if (t > 0) bar_sync(N_TURN + wg, 256);
        float acc[112];
        acc_zero(acc);
#pragma unroll
        for (int i = 0; i < 14; i++) {
            if (t < 2 && (i & 1) == 0) mbar_wait_warp(bars + WB_SLAB + 8 * (i >> 1), 0, t0a);
            if (t == 0 && threadIdx.x == 0 && (i == 0 || i == 12)) TR(131, 128 + w * 8 + 1 + i / 12);
            mbar_wait_warp(bars + WB_FULL + 8 * (i % 7), i / 7, t0a);
            if (i == 13 && t < 31) bar_arrive(N_TURN + (wg ^ 1), 256);
            wg_fence();
#pragma unroll
            for (int kk = 0; kk < 2; kk++)
                wgmma_n224<0, 0>(acc, mdesc(sb + W_RING + (i % 7) * 4096 + kk * 2048, 1024, 128, 0), mdesc(sb + (2 * i + kk) * 7168, 3584, 128, 0), 1);
            wg_commit();
            if (i >= 2) {
                wg_wait<2>();
                if (lane == 0) mbar_arrive(bars + WB_EMPTY + 8 * ((i - 2) % 7));
            }
        }
        wg_wait<1>();
        if (lane == 0) mbar_arrive(bars + WB_EMPTY + 8 * 5);
        wg_wait<0>();
        acc_fence(acc);
        if (lane == 0) {
            mbar_arrive(bars + WB_EMPTY + 8 * 6);
            if (t >= 30) mbar_arrive(bars + WB_WDONE);
        }
        if (t == 0 && threadIdx.x == 0) TR(131, 128 + w * 8 + 3);
        uint8_t* dst = g_kv + (size_t)((2 * t + (warp >> 1)) * 16 + h) * HBLK + (TYPE ? VO_OFF + 2 * half * QBLK : 2 * half * CHUNK) + lane * 16;
        if (!TYPE) {
#pragma unroll
            for (int qq = 0; qq < 2; qq++)
#pragma unroll
                for (int hi = 0; hi < 2; hi++) {
                    uint8_t* d = dst + qq * CHUNK + (2 * (warp & 1) + hi) * 1792;
                    const float* a = acc + 56 * qq + 2 * hi;
#pragma unroll
                    for (int c = 0; c < 3; c++)
                        st_stream(d + c * 512, make_uint4(pack2(a[16 * c], a[16 * c + 1]), pack2(a[16 * c + 4], a[16 * c + 5]),
                                                          pack2(a[16 * c + 8], a[16 * c + 9]), pack2(a[16 * c + 12], a[16 * c + 13])));
                    *(uint2*)(d + 1536 - lane * 8) = make_uint2(pack2(a[48], a[49]), pack2(a[52], a[53]));
                }
        } else {
#pragma unroll
            for (int c = 0; c < 14; c++) {
                const float* a = acc + 8 * c;
                st_stream(dst + (c / 7) * QBLK + (warp & 1) * 3584 + (c % 7) * 512,
                          make_uint4(movm(pack2(a[0], a[1])), movm(pack2(a[4], a[5])), movm(pack2(a[2], a[3])), movm(pack2(a[6], a[7]))));
            }
        }
        bar_sync(N_WG + wg, 128);
        if ((threadIdx.x & 127) == 0) {
            if (t == 0) TR(131, 128 + w * 8 + 4);
            st_rel(&g_ctl.prog[(w * 2 + wg) * 8], e * 64 + (t >> 1) + 1);
            TR(132 + w, t);
        }
    }
}
__device__ __forceinline__ void kv_producer(uint32_t sb, int w, unsigned e, int pw) {
    const uint32_t bars = sb + W_BAR, t0a = sb + W_MISC + WM_T0;
    if (pw == 0) {
        flag_wait((w & 2) ? &g_ctl.cntB[(w >> 2) * 32] : &g_ctl.cntA[(w >> 2) * 32], 4 * e, t0a);
        TR(131, 128 + w * 8);
        fence_async();
#pragma unroll 1
        for (int i = 0; i < 7; i++) {
            mbar_expect(bars + WB_SLAB + 8 * i, 28672);
            bulk_load(sb + i * 28672, g_wall + (size_t)w * SLAB + i * 28672, 28672, bars + WB_SLAB + 8 * i);
        }
    }
    flag_wait(g_ctl.cntLN, NWORK * e, t0a);
    if (pw) TR(131, 128 + w * 8 + 5);
    fence_async();
    int slot = pw, use = 0;
#pragma unroll 1
    for (int n = pw; n < 448; n += 2) {
        mbar_wait(bars + WB_EMPTY + 8 * slot, (use & 1) ^ 1, t0a);
        mbar_expect(bars + WB_FULL + 8 * slot, 4096);
        bulk_load(sb + W_RING + slot * 4096, g_xn + n * 4096, 4096, bars + WB_FULL + 8 * slot);
        if (slot == 0 && (use & 1) == 0) bulk_prefetch(g_xn + (((use >> 1) + 3) & 31) * XTILE + w * 896, 896);
        slot += 2;
        if (slot >= 7) { slot -= 7; use++; }
    }
}

__device__ __forceinline__ uint32_t ffn_task(unsigned i) {
    if (i < 70) return (T_UP << 14) | ((i / 14) << 4) | (i % 14);
    if (i < 246) {
        const unsigned a = (i - 70) >> 4, r = (i - 70) & 15;
        return r < 2 ? (T_DOWN << 14) | (a << 4) | r : (T_UP << 14) | ((a + 5) << 4) | (r - 2);
    }
    return (T_DOWN << 14) | ((11 + ((i - 246) >> 1)) << 4) | (i & 1);
}
__device__ __forceinline__ uint32_t next_task(unsigned e, bool ffn, int rank, bool& ffn_left, uint32_t t0a) {
    unsigned* q = g_ctl.queue[e & 1];
    while (!expired(t0a)) {
        const unsigned hp = ld_rlx(q + 32);
        if (hp >= NATT && !ffn_left) break;
        const int sp = (int)(min(hp + rank, NATT - 1u) >> 1) - (ffn && ffn_left ? 0 : P_AHEAD);
        if (hp < NATT && (int)(ld_rlx(&g_ctl.cntM[max(sp, 0) * 32]) - 64 * e) >= 0) {
            const unsigned i = atomicAdd(q + 32, 1u);
            if (i < NATT) return (T_PV << 14) | ((i >> 1) << 4) | (i & 1);
        } else if (ffn_left && (ffn || hp >= NATT)) {
            const unsigned i = atomicAdd(q, 1u);
            if (i < NFFN) return ffn_task(i);
            ffn_left = false;
        } else {
            rank >>= 1;
        }
    }
    return 0xFFFFu;
}
__device__ __forceinline__ void task_scheduler(uint32_t sb, unsigned e, int ffn_until, int rank) {
    const uint32_t bars = sb + W_BAR, misc = sb + W_MISC, t0a = misc + WM_T0;
    bool ffn_left = true;
#pragma unroll 1
    for (int i = 0;; i++) {
        mbar_wait(bars + WB_NEXT, (i & 1) ^ 1, t0a);
        mbar_wait(bars + WB_TEMPTY + 8 * (i & 1), ((i >> 1) & 1) ^ 1, t0a);
        uint32_t code = next_task(e, i < ffn_until, rank, ffn_left, t0a);
        if (code != 0xFFFFu) {
            const int type = code >> 14, a = (code >> 4) & 1023;
            flag_wait(type == T_UP ? g_ctl.cntLN : type == T_DOWN ? &g_ctl.cntH[a * 32] : &g_ctl.cntM[a * 32],
                      (type == T_UP ? NWORK : type == T_DOWN ? 14 : 64) * e, t0a);
            if (type == T_PV) {
                const unsigned* tk = &g_ctl.ticket[4 * a + (code & 1)];
                const unsigned up = ld_rlx(&g_ctl.cntH[(a >> 2) * 32]), t0 = ld_rlx(tk), t1 = ld_rlx(tk + 2);
                asm volatile("fence.acquire.gpu;" ::: "memory");
                if (t0 & t1 & 1) code |= GATE_READY;
                else if ((int)(up - 14 * e) >= 0) code |= GATE_NEAR;
            }
        }
        sts32(misc + WM_TASK + 4 * (i & 1), code);
        mbar_arrive(bars + WB_TFULL + 8 * (i & 1));
        if (code == 0xFFFFu) break;
    }
}
__device__ __forceinline__ void task_producer(uint32_t sb, const Maps* maps, const __nv_bfloat16* x) {
    const uint32_t bars = sb + W_BAR, misc = sb + W_MISC, t0a = misc + WM_T0;
    int n = 0, dn = 0;
#pragma unroll 1
    for (int i = 0;; i++) {
        mbar_wait(bars + WB_TFULL + 8 * (i & 1), (i >> 1) & 1, t0a);
        const uint32_t code = lds32(misc + WM_TASK + 4 * (i & 1));
        mbar_arrive(bars + WB_TEMPTY + 8 * (i & 1));
        if (code == 0xFFFFu || expired(t0a)) break;
        const int type = (code >> 14) & 3, a = (code >> 4) & 1023, b = code & 15;
        fence_async();
        const int nk = type == T_UP ? 7 : type == T_DOWN ? 28 : 8;
        const uint8_t* src = type == T_UP ? g_xn + (size_t)(2 * a) * XTILE : type == T_DOWN ? g_h + (size_t)(2 * a) * HTILE
                           : g_kv + (size_t)a * 16 * HBLK + VO_OFF + 2 * b * QBLK;
        if (type == T_PV) {
            mbar_wait(bars + WB_DEMPTY, (dn & 1) ^ 1, t0a);
            mbar_expect(bars + WB_DFULL, 32768);
            bulk_load(sb + W_DBUF, g_p + (size_t)a * 32768, 32768, bars + WB_DFULL);
            dn++;
        }
#pragma unroll 1
        for (int kc = 0; kc < nk; kc++, n++) {
            if (kc == nk - 4) {
                mbar_arrive(bars + WB_NEXT);
                if (type == T_DOWN) bulk_prefetch(b ? (const void*)(g_sx + (size_t)a * 128 * D * 2) : (const void*)(x + (size_t)a * 128 * D), 128 * D * 2);
            }
            const uint32_t full = bars + WB_GFULL + 8 * (n & 3), dst = sb + (n & 3) * W_STAGE;
            mbar_wait(bars + WB_GEMPTY + 8 * (n & 3), ((n >> 2) & 1) ^ 1, t0a);
            if (type == T_PV) {
                mbar_expect(full, 4 * QBLK);
                bulk_load_stream(dst, src + 2 * kc * HBLK, 2 * QBLK, full);
                bulk_load_stream(dst + 2 * QBLK, src + (2 * kc + 1) * HBLK, 2 * QBLK, full);
            } else {
                mbar_expect(full, type == T_UP ? 49152 : 45056);
                if (type == T_UP) {
                    tma3(dst + 16384, &maps->g, 0, 64 * kc, 2 * b, full);
                    tma3(dst + 32768, &maps->u, 0, 64 * kc, 2 * b, full);
                } else {
                    tma3(dst + 16384, &maps->d, 0, 64 * kc, 7 * b, full);
                }
                bulk_load(dst, src + kc * 8192, 8192, full);
                bulk_load(dst + 8192, src + (type == T_UP ? XTILE : HTILE) + kc * 8192, 8192, full);
            }
        }
    }
}

template <int NK, int N, class F>
__device__ __forceinline__ void gemm_mainloop(uint32_t sb, int& n, float (&acc)[N], F issue TTARG) {
    const int lane = threadIdx.x & 31;
    const uint32_t bars = sb + W_BAR, t0a = sb + W_MISC + WM_T0;
#pragma unroll 1
    for (int kc = 0; kc < NK; kc++, n++) {
        mbar_wait_warp(bars + WB_GFULL + 8 * (n & 3), (n >> 2) & 1, t0a);
        if (kc == 0) TT(2);
        wg_fence();
        issue(sb + (n & 3) * W_STAGE, kc);
        wg_commit();
        if (kc > 0) {
            wg_wait<1>();
            if (lane == 0) mbar_arrive(bars + WB_GEMPTY + 8 * ((n - 1) & 3));
        }
    }
    wg_wait<0>();
    acc_fence(acc);
    TT(3);
    if (lane == 0) mbar_arrive(bars + WB_GEMPTY + 8 * ((n - 1) & 3));
}

__device__ __forceinline__ void task_up(uint32_t sb, int& n, int& pn, int a, int b TTARG) {
    const int lane = threadIdx.x & 31, warp = (threadIdx.x >> 5) & 3, wg = threadIdx.x >> 7;
    float acc[128];
    acc_zero(acc);
    gemm_mainloop<7>(sb, n, acc, [&](uint32_t st, int kc) {
#pragma unroll
        for (int kk = 0; kk < 4; kk++)
            wgmma_n256<0, 1>(acc, mdesc(st + wg * 8192 + kk * 2048, 1024, 128, 0), mdesc(st + 16384 + kk * 2048, 8192, 1024, 1), (kc | kk) != 0);
    } TTPASS);
    uint32_t* dst = (uint32_t*)(g_h + (size_t)(2 * a + wg) * HTILE + (16 * b * 8 + 2 * warp) * 128) + lane;
#pragma unroll
    for (int u = 0; u < 16; u++)
#pragma unroll
        for (int hi = 0; hi < 2; hi++) {
            const uint32_t up = pack2(acc[64 + 4 * u + 2 * hi], acc[64 + 4 * u + 2 * hi + 1]);
            dst[(u * 8 + hi) * 32] = mul2(pack2(silu(acc[4 * u + 2 * hi]), silu(acc[4 * u + 2 * hi + 1])), up);
        }
    post(sb, pn, (T_UP << 14) | (a << 4));
}

__device__ __forceinline__ uint4 quad_transpose(uint32_t a0, uint32_t a1, uint32_t a2, uint32_t a3, bool o1, bool o2) {
    const uint32_t s0 = __shfl_xor_sync(0xffffffffu, o1 ? a0 : a1, 1), s1 = __shfl_xor_sync(0xffffffffu, o1 ? a2 : a3, 1);
    const uint32_t b0 = o1 ? s0 : a0, b1 = o1 ? a1 : s0, b2 = o1 ? s1 : a2, b3 = o1 ? a3 : s1;
    const uint32_t t0 = __shfl_xor_sync(0xffffffffu, o2 ? b0 : b2, 2), t1 = __shfl_xor_sync(0xffffffffu, o2 ? b1 : b3, 2);
    return o2 ? make_uint4(t0, t1, b2, b3) : make_uint4(b0, b1, t0, t1);
}

__device__ __forceinline__ void task_down(uint32_t sb, int& n, int a, int b, const __nv_bfloat16* x, __nv_bfloat16* out TTARG) {
    const int lane = threadIdx.x & 31, warp = (threadIdx.x >> 5) & 3, wg = threadIdx.x >> 7;
    float acc[112];
    acc_zero(acc);
    gemm_mainloop<28>(sb, n, acc, [&](uint32_t st, int kc) {
#pragma unroll
        for (int kk = 0; kk < 4; kk++)
            wgmma_n224<0, 1>(acc, mdesc(st + wg * 8192 + kk * 2048, 1024, 128, 0), mdesc(st + 16384 + kk * 1024, 4096, 512, 2), (kc | kk) != 0);
    } TTPASS);
    const int r16 = 8 * a + 4 * wg + warp;
    const int off = ((16 * r16 + (lane >> 2)) * D + 224 * b + 8 * (lane & 3)) * 2;
    uint4 gv[7][2];
#pragma unroll
    for (int u = 0; u < 7; u++)
#pragma unroll
        for (int hi = 0; hi < 2; hi++) {
            uint32_t p[4];
#pragma unroll
            for (int i = 0; i < 4; i++) {
                const uint32_t dp = pack2(acc[16 * u + 4 * i + 2 * hi], acc[16 * u + 4 * i + 2 * hi + 1]);
                p[i] = pack2(silu(bflo(dp)), silu(bfhi(dp)));
            }
            gv[u][hi] = quad_transpose(p[0], p[1], p[2], p[3], lane & 1, lane & 2);
            *(uint4*)(g_gx + off + hi * 16 * D + 64 * u) = gv[u][hi];
        }
    __syncwarp();
    unsigned old = 0;
    if (lane == 0) asm volatile("atom.acq_rel.gpu.global.add.u32 %0, [%1], 1;" : "=r"(old) : "l"(&g_ctl.ticket[2 * r16 + b]) : "memory");
    old = __shfl_sync(0xffffffffu, old, 0);
    if (old & 1) {
        uint4 sv[7][2], xv[7][2];
#pragma unroll
        for (int u = 0; u < 7; u++)
#pragma unroll
            for (int hi = 0; hi < 2; hi++) {
                sv[u][hi] = ldcg128(g_sx + off + hi * 16 * D + 64 * u);
                xv[u][hi] = ldcg128((const uint8_t*)x + off + hi * 16 * D + 64 * u);
            }
#pragma unroll
        for (int u = 0; u < 7; u++)
#pragma unroll
            for (int hi = 0; hi < 2; hi++) *(uint4*)((uint8_t*)out + off + hi * 16 * D + 64 * u) = combine4(xv[u][hi], sv[u][hi], gv[u][hi]);
    }
}

__device__ __forceinline__ void task_pv(uint32_t sb, int& n, int& dn, int& pn, uint32_t code, const __nv_bfloat16* x, __nv_bfloat16* out TTARG) {
    const int seg = (code >> 4) & 1023, half = code & 1;
    const int lane = threadIdx.x & 31, w = threadIdx.x >> 5;
    const uint32_t bars = sb + W_BAR, t0a = sb + W_MISC + WM_T0;
    const int off = ((32 * seg + (lane >> 2)) * D + 224 * half + 32 * min(w, 6) + 8 * (lane & 3)) * 2;
    uint4 xv[4], gv[4];
    if (code & (GATE_READY | GATE_NEAR)) {
#pragma unroll
        for (int i = 0; i < 4; i++) { xv[i] = ldcg128((const uint8_t*)x + off + i * 16 * D); gv[i] = ldcg128(g_gx + off + i * 16 * D); }
    }
    mbar_wait_warp(bars + WB_DFULL, dn & 1, t0a);
    TT(2);
    dn++;
    float o[2][4][4];
#pragma unroll
    for (int i = 0; i < 2; i++)
#pragma unroll
        for (int j = 0; j < 4; j++) o[i][j][0] = o[i][j][1] = o[i][j][2] = o[i][j][3] = 0.f;
    const int c0 = 2 * min(w, 6), c1 = c0 + 1;
    const uint32_t q0 = sb + (c0 / 7) * QBLK, q1 = sb + (c1 / 7) * QBLK;
    const uint32_t t0 = pin(q0 + (c0 % 7) * 512 + lane * 16), t1 = pin(q1 + (c1 % 7) * 512 + lane * 16);
    const uint32_t u0 = pin(q0 + CHUNK + (c0 % 7) * 256 + lane * 8), u1 = pin(q1 + CHUNK + (c1 % 7) * 256 + lane * 8);
    const uint32_t pa = pin(sb + W_DBUF + lane * 16);
    const bool first = pin(lane) == 0;
    if (w < 7) {
#pragma unroll 1
        for (int kc = 0; kc < 8; kc++, n++) {
            mbar_wait_warp(bars + WB_GFULL + 8 * (n & 3), (n >> 2) & 1, t0a);
            uint4 p[2][4], a[2][2], b[2][2];
            uint2 m[2][2];
#pragma unroll
            for (int i = 0; i < 2; i++) {
                const uint32_t st = (n & 3) * W_STAGE + i * 2 * QBLK;
#pragma unroll
                for (int k = 0; k < 4; k++) p[i][k] = lds128(pa + (2 * kc + i) * 2048 + k * 512);
                a[i][0] = lds128(t0 + st); a[i][1] = lds128(t1 + st);
                b[i][0] = lds128(t0 + st + 3584); b[i][1] = lds128(t1 + st + 3584);
                m[i][0] = lds64(u0 + st); m[i][1] = lds64(u1 + st);
            }
#pragma unroll
            for (int i = 0; i < 2; i++) {
#pragma unroll
                for (int rt = 0; rt < 2; rt++)
#pragma unroll
                    for (int c = 0; c < 2; c++) {
                        mma16(o[rt][2 * c], p[i][rt].x, p[i][rt].y, p[i][rt].z, p[i][rt].w, a[i][c].x, a[i][c].z);
                        mma16(o[rt][2 * c + 1], p[i][rt].x, p[i][rt].y, p[i][rt].z, p[i][rt].w, a[i][c].y, a[i][c].w);
                    }
#pragma unroll
                for (int c = 0; c < 2; c++) {
                    mma8(o[0][2 * c], p[i][3].x, p[i][3].y, m[i][c].x);
                    mma8(o[0][2 * c + 1], p[i][3].x, p[i][3].y, m[i][c].y);
                    mma16(o[1][2 * c], p[i][2].x, p[i][2].y, p[i][2].z, p[i][2].w, b[i][c].x, b[i][c].z);
                    mma16(o[1][2 * c + 1], p[i][2].x, p[i][2].y, p[i][2].z, p[i][2].w, b[i][c].y, b[i][c].w);
                }
#pragma unroll
                for (int c = 0; c < 2; c++) {
                    mma8(o[1][2 * c], p[i][3].z, p[i][3].w, m[i][c].x);
                    mma8(o[1][2 * c + 1], p[i][3].z, p[i][3].w, m[i][c].y);
                }
            }
            __syncwarp();
            if (first) mbar_arrive(bars + WB_GEMPTY + 8 * (n & 3));
        }
    } else {
#pragma unroll 1
        for (int kc = 0; kc < 8; kc++, n++) {
            mbar_wait_warp(bars + WB_GFULL + 8 * (n & 3), (n >> 2) & 1, t0a);
            if (first) mbar_arrive(bars + WB_GEMPTY + 8 * (n & 3));
        }
    }
    TT(3);
    if (first) mbar_arrive(bars + WB_DEMPTY);
    uint4 sv[4];
#pragma unroll
    for (int i = 0; i < 4; i++) {
        const float (&v)[4][4] = o[i >> 1];
        const int e = 2 * (i & 1);
        sv[i] = quad_transpose(pack2(v[0][e], v[0][e + 1]), pack2(v[1][e], v[1][e + 1]), pack2(v[2][e], v[2][e + 1]), pack2(v[3][e], v[3][e + 1]), lane & 1, lane & 2);
        if (w < 7 && !(code & GATE_READY)) *(uint4*)(g_sx + off + i * 16 * D) = sv[i];
    }
    uint2 tk = make_uint2(code / GATE_READY, code / GATE_READY);
    if (code & GATE_NEAR) {
        const uint32_t ta = sb + W_MISC + WM_TICK;
        bar_sync(N_CONS, 256);
        if (threadIdx.x >= 254) {
            unsigned old;
            asm volatile("atom.acq_rel.gpu.global.add.u32 %0, [%1], 1;" : "=r"(old) : "l"(&g_ctl.ticket[2 * (2 * seg + (threadIdx.x & 1)) + half]) : "memory");
            sts32(ta + 4 * (threadIdx.x & 1), old);
        }
        bar_sync(N_CONS, 256);
        tk = lds64(ta);
        if ((tk.x | tk.y) & 1) {
#pragma unroll
            for (int i = 0; i < 4; i++) gv[i] = ldcg128(g_gx + off + i * 16 * D);
        }
    } else {
        post(sb, pn, code);
    }
#pragma unroll
    for (int i = 0; i < 4; i++)
        if (w < 7 && ((i < 2 ? tk.x : tk.y) & 1)) *(uint4*)((uint8_t*)out + off + i * 16 * D) = combine4(xv[i], sv[i], gv[i]);
}

__global__ void __launch_bounds__(384, 1)
work_kernel(const __grid_constant__ Maps maps, const __nv_bfloat16* __restrict__ x, __nv_bfloat16* __restrict__ out, int mode) {
    extern __shared__ __align__(1024) uint8_t smem[];
    const uint32_t sb = (uint32_t)__cvta_generic_to_shared(smem);
    const uint32_t bars = sb + W_BAR, misc = sb + W_MISC, t0a = misc + WM_T0;
    const int tid = threadIdx.x, lane = tid & 31, warp = tid >> 5, wg = tid >> 7, w = blockIdx.x;
    const bool pro = (mode & 1) && w < 64, kvp = (mode & 2) && w < 64;
    if (tid == 224 && pro) ab_issue<1>(&maps, w >> 2, w & 3, sb, bars);
    uint4 xv[14];
    if (pro && wg == 2) ln_load(xv, x, w, warp - 8, lane);
    if (tid == 0) {
        sts32(t0a, clk32());
    } else if (tid == 32) {
        TR((mode & 8) ? 198 : 131, w);
        for (int i = 0; i < 7; i++) { mbar_init(bars + WB_SLAB + 8 * i, 1); mbar_init(bars + WB_FULL + 8 * i, 1); mbar_init(bars + WB_EMPTY + 8 * i, 4); }
        for (int i = 0; i < 4; i++) { mbar_init(bars + WB_GFULL + 8 * i, 1); mbar_init(bars + WB_GEMPTY + 8 * i, 8); }
        for (int i = 0; i < 2; i++) {
            mbar_init(bars + WB_TFULL + 8 * i, 1); mbar_init(bars + WB_TEMPTY + 8 * i, 9);
            mbar_init(bars + WB_PFULL + 8 * i, 8); mbar_init(bars + WB_PEMPTY + 8 * i, 1);
        }
        mbar_init(bars + WB_NEXT, 1);
        mbar_init(bars + WB_DFULL, 1);
        mbar_init(bars + WB_DEMPTY, 8);
        mbar_init(bars + WB_WDONE, 8);
        fence_init();
    }
    asm volatile("griddepcontrol.launch_dependents;");
    const unsigned e = (mode & 8) ? ld_rlx(g_ctl.cntA) >> 2 : ld_rlx(g_ctl.epoch) + 1;
    __syncthreads();
    if (pro) {
        if (wg == 2) {
            ln_finish(xv, w, warp - 8, lane);
            bar_sync(N_LN, 128);
        }
        if (tid == 352) red_rel(g_ctl.cntLN, 1);
        __syncwarp();
        const float mx = ab_compute<1, 3>(&maps, w >> 2, w & 3, sb, bars, wg, N_WG + wg, t0a);
        const uint32_t m = __reduce_max_sync(0xffffffffu, __float_as_uint(mx));
        if (lane == 0) sts32(misc + WM_MAX + 4 * warp, m);
        __syncthreads();
        if (warp == 11) {
            const uint32_t mm = __reduce_max_sync(0xffffffffu, lds32(misc + WM_MAX + 4 * min(lane, 11)));
            if (lane == 0) {
                g_ctl.bmax[w] = mm;
                red_rel(&g_ctl.cntB[(w >> 2) * 32], 1);
                TR(129, 64 + w);
            }
            __syncwarp();
        }
    } else if ((mode & 1) && tid == 352) {
        red_rel(g_ctl.cntLN, 1);
    }
    if (wg == 2) {
        reg_dec<40>();
        if (warp == 10 && (mode & 4)) publisher(sb, x, out);
        if (lane == 0 && warp < 10) {
            if (kvp) kv_producer(sb, w, e, warp - 8);
            if (mode & 4) {
                if (warp == 9) {
                    const bool att = !(mode & 8) && w >= 64 + FFN_SPARES;
                    task_scheduler(sb, e, att ? SPARE_FFN : 1 << 30, att ? 0 : RANK0 + w);
                } else {
                    if (kvp) mbar_wait(bars + WB_WDONE, 0, t0a);
                    task_producer(sb, &maps, x);
                }
            }
        }
    } else {
        reg_inc<232>();
        if (kvp) {
            kv_consumer(sb, w, e);
        }
        if (mode & 4) {
            int n = 0, dn = 0, pn = 0;
#pragma unroll 1
            for (int i = 0;; i++) {
                mbar_wait_warp(bars + WB_TFULL + 8 * (i & 1), (i >> 1) & 1, t0a);
                const uint32_t code = lds32(misc + WM_TASK + 4 * (i & 1));
                if (code == 0xFFFFu || expired(t0a)) break;
                const int type = (code >> 14) & 3, a = (code >> 4) & 1023, b = code & 15;
                if (type == T_UP) task_up(sb, n, pn, a, b TTPASS);
                else if (type == T_DOWN) task_down(sb, n, a, b, x, out TTPASS);
                else task_pv(sb, n, dn, pn, code, x, out TTPASS);
                __syncwarp();
                if (lane == 0) mbar_arrive(bars + WB_TEMPTY + 8 * (i & 1));
            }
            post(sb, pn, 0xFFFFu);
            if (tid == 0) TR((mode & 8) ? 199 : 197, w);
        }
    }
}

typedef CUresult (*EncodeFn)(CUtensorMap*, CUtensorMapDataType, cuuint32_t, void*, const cuuint64_t*, const cuuint64_t*,
                             const cuuint32_t*, const cuuint32_t*, CUtensorMapInterleave, CUtensorMapSwizzle,
                             CUtensorMapL2promotion, CUtensorMapFloatOOBfill);

void encode(EncodeFn fn, CUtensorMap* m, void* p, int rank, cuuint64_t d0, cuuint64_t d1, cuuint64_t d2, cuuint64_t s1,
            cuuint64_t s2, cuuint32_t b0, cuuint32_t b1, cuuint32_t b2, CUtensorMapSwizzle swz) {
    const cuuint64_t dims[3] = {d0, d1, d2}, strides[2] = {s1, s2};
    const cuuint32_t box[3] = {b0, b1, b2}, es[3] = {1, 1, 1};
    fn(m, CU_TENSOR_MAP_DATA_TYPE_BFLOAT16, rank, p, dims, strides, box, es, CU_TENSOR_MAP_INTERLEAVE_NONE, swz,
       CU_TENSOR_MAP_L2_PROMOTION_L2_256B, CU_TENSOR_MAP_FLOAT_OOB_FILL_NONE);
}

}

extern "C" void kernel_launch(void* const* d_in, const int* in_sizes, int n_in, void* d_out, int out_size) {
    static EncodeFn fn = nullptr;
    static Maps maps;
    static const void* encoded[7];
    if (!fn) {
        cudaDriverEntryPointQueryResult qr;
        cudaGetDriverEntryPoint("cuTensorMapEncodeTiled", (void**)&fn, cudaEnableDefault, &qr);
        cudaFuncSetAttribute(chain_kernel, cudaFuncAttributeMaxDynamicSharedMemorySize, C_SMEM);
        void* wall;
        cudaGetSymbolAddress(&wall, g_wall);
        encode(fn, &maps.w, wall, 3, 64, 28, 56 * 64, 128, 3584, 64, 14, 14, CU_TENSOR_MAP_SWIZZLE_NONE);
        cudaFuncSetAttribute(work_kernel, cudaFuncAttributeMaxDynamicSharedMemorySize, W_SMEM);
    }
    const int widx[7] = {2, 3, 4, 5, 8, 9, 10};
    bool same = true;
    for (int i = 0; i < 7; i++) same = same && encoded[i] == d_in[widx[i]];
    if (!same) {
        encode(fn, &maps.q, d_in[2], 3, 64, 448, 64, 8192, 128, 64, 64, 4, CU_TENSOR_MAP_SWIZZLE_128B);
        encode(fn, &maps.k, d_in[3], 3, 64, 448, 64, 8192, 128, 64, 112, 4, CU_TENSOR_MAP_SWIZZLE_128B);
        encode(fn, &maps.v, d_in[4], 3, 64, 448, 64, 8192, 128, 64, 112, 4, CU_TENSOR_MAP_SWIZZLE_128B);
        encode(fn, &maps.o, d_in[5], 2, 448, 4096, 1, 896, 0, 64, 256, 1, CU_TENSOR_MAP_SWIZZLE_128B);
        encode(fn, &maps.g, d_in[8], 3, 64, 448, 28, 3584, 128, 64, 64, 2, CU_TENSOR_MAP_SWIZZLE_128B);
        encode(fn, &maps.u, d_in[9], 3, 64, 448, 28, 3584, 128, 64, 64, 2, CU_TENSOR_MAP_SWIZZLE_128B);
        encode(fn, &maps.d, d_in[10], 3, 32, 1792, 14, 896, 64, 32, 64, 7, CU_TENSOR_MAP_SWIZZLE_64B);
        for (int i = 0; i < 7; i++) encoded[i] = d_in[widx[i]];
    }
    const __nv_bfloat16* x = (const __nv_bfloat16*)d_in[0];
    const __nv_bfloat16* mem0 = (const __nv_bfloat16*)d_in[1];
    __nv_bfloat16* out = (__nv_bfloat16*)d_out;

    cudaLaunchAttribute pdl[1];
    pdl[0].id = cudaLaunchAttributeProgrammaticStreamSerialization;
    pdl[0].val.programmaticStreamSerializationAllowed = 1;
    cudaLaunchConfig_t cc = {}, cw = {};
    cc.gridDim = dim3(64); cc.blockDim = dim3(512); cc.dynamicSmemBytes = C_SMEM; cc.stream = cudaStreamPerThread;
    cw.gridDim = dim3(NWORK); cw.blockDim = dim3(384); cw.dynamicSmemBytes = W_SMEM; cw.stream = cudaStreamPerThread;
    cudaLaunchKernelEx(&cc, chain_kernel, maps, x, mem0, 3);
    cw.attrs = pdl; cw.numAttrs = 1;
    cudaLaunchKernelEx(&cw, work_kernel, maps, x, out, 7);
    cw.gridDim = dim3(NTAIL);
    cudaLaunchKernelEx(&cw, work_kernel, maps, x, out, 4 | 8);
}
```
